```python
import torch

def _softmax(x, axis=-1):
    return torch.softmax(x, dim=axis)
def _gelu(x):
    return torch.nn.functional.gelu(x, approximate="tanh")
def _silu(x):
    return torch.nn.functional.silu(x)
def _sigmoid(x):
    return torch.sigmoid(x)
def _layernorm(x, axis=-1, eps=1e-5):
    m = x.mean(dim=axis, keepdim=True)
    v = x.var(dim=axis, keepdim=True, unbiased=False)
    return (x - m) / torch.sqrt(v + eps)
def _scatter_add(tgt, idx, src, axis=0):
    return tgt.clone().index_add_(axis, idx, src)
def _segment_sum(src, seg, n):
    out = torch.zeros((n,) + src.shape[1:], dtype=src.dtype)
    return out.index_add_(0, seg, src)
def _pad(x, pw):
    flat = tuple(v for pair in reversed(pw) for v in pair)
    return torch.nn.functional.pad(x, flat)

kernel_name = 'standalone__kv_cache_quant_int4_int2_kv_with_per_channel_or_per_token_scales__prompt'

def setup_inputs():

    _w = (lambda a: (lambda t: t.to(torch.bfloat16) if t.is_floating_point() else t)(torch.as_tensor(a)))
    B = 1
    Sq = 2048
    Skv = 2048
    Hq = 32
    Hkv = 32
    Dh = 192
    bits = 8
    G = 64
    if G <= 0 or G >= Skv:
        G = max(1, Skv // 2)
    Skv = (Skv // G) * G
    ngk = Skv // G
    qmax = (1 << bits) - 1
    return {
        "q": _w((lambda *s: torch.randn(*s, dtype=torch.bfloat16) * 0.2)(B, Hq, Sq, Dh)),
        "qk": _w(torch.randint(0, qmax + 1, (B, Hkv, Skv, Dh)).to(torch.int32)),
        "qv": _w(torch.randint(0, qmax + 1, (B, Hkv, Skv, Dh)).to(torch.int32)),
        "k_scales": _w(torch.abs((lambda *s: torch.randn(*s, dtype=torch.bfloat16) * 0.2)(B, Hkv, ngk, Dh)) * 0.05 + 0.02),
        "k_zeros": _w((lambda *s: torch.randn(*s, dtype=torch.bfloat16) * 0.2)(B, Hkv, ngk, Dh) + float(qmax) / 2.0),
        "v_scales": _w(torch.abs((lambda *s: torch.randn(*s, dtype=torch.bfloat16) * 0.05)(B, Hkv, Skv, 1)) * 0.05 + 0.02),
        "v_zeros": _w((lambda *s: torch.randn(*s, dtype=torch.bfloat16) * 0.05)(B, Hkv, Skv, 1) + float(qmax) / 2.0),
    }

def reference(q, qk, qv, k_scales, k_zeros, v_scales, v_zeros):
    B, Hq, Sq, Dh = q.shape
    Hkv, Skv = qk.shape[1], qk.shape[2]
    ngk = k_scales.shape[2]
    G = Skv // ngk
    ks = (lambda x, n, axis: torch.repeat_interleave(x, n, dim=axis))(k_scales, G, axis=2)
    kz = (lambda x, n, axis: torch.repeat_interleave(x, n, dim=axis))(k_zeros, G, axis=2)
    k = ((lambda x, dt: x.to(dt))(qk, q.dtype) - kz) * ks
    v = ((lambda x, dt: x.to(dt))(qv, q.dtype) - v_zeros) * v_scales
    rep = Hq // Hkv
    if rep > 1:
        k = (lambda x, n, axis: torch.repeat_interleave(x, n, dim=axis))(k, rep, axis=1)
        v = (lambda x, n, axis: torch.repeat_interleave(x, n, dim=axis))(v, rep, axis=1)
    scale = float(Dh) ** -0.5
    logits = torch.einsum("bhqd,bhkd->bhqk", q, k) * scale
    p = _softmax(logits, axis=-1)
    o = torch.einsum("bhqk,bhkd->bhqd", p, v)
    return o
```

```cpp
#include <cuda_runtime.h>
#include <cuda_bf16.h>
#include <cuda.h>
#include <stdint.h>

#define LEAD 2
#define Q_T0 1400
#define Q_DT 250
#define POLL_T 4100
#define PF_TK 4500
#define PF_TV 5100
#define PF_DT 1100
#define PFD 1
#define DQ_TK 5600
#define DQ_TV 5800
#define WPOLL 350
#define KOFF 0.5f
#define QPF 5
#define VEXP (-10)
#define VOFF 1.25f
#define TF0 29
#define SPIN_LIMIT (1u << 22)

namespace {

constexpr int CLUSTER = 2;
constexpr int NH = 32, SEQ = 2048, DH = 192;
constexpr int NGROUP = 8, GSIZE = 16, TOTAL = 64;
constexpr int NCTA = NGROUP * GSIZE;
constexpr uint32_t TILE = 128 * DH * 2;
constexpr uint32_t SUB = 16384;
constexpr int KSLOTS = 5;
constexpr int RING = 8;
static_assert(RING >= 2 * LEAD + 4, "a ring slot may only be rewritten after every CTA of the group has loaded it");

constexpr uint32_t SM_Q = 0;
constexpr uint32_t SM_K = 49152;
constexpr uint32_t SM_V = SM_K + KSLOTS * SUB;
constexpr uint32_t SM_BAR = SM_V + 2 * TILE;
constexpr uint32_t B_KFULL = SM_BAR, B_KEMPTY = B_KFULL + 8 * KSLOTS;
constexpr uint32_t B_VFULL = B_KEMPTY + 8 * KSLOTS, B_VEMPTY = B_VFULL + 16;
constexpr uint32_t B_QFULL = B_VEMPTY + 16;
constexpr uint32_t B_UNIT = B_QFULL + 16;
constexpr uint32_t B_ROLE = B_UNIT + 64, SM_ROLE = B_ROLE + 8;
constexpr uint32_t SM_LAT = B_ROLE + 16;
constexpr uint32_t SM_OFF = SM_LAT + 32;
constexpr uint32_t SM_PROG = SM_OFF + 80;
constexpr uint32_t SM_QBIG = SM_PROG + 4;
constexpr uint32_t SM_REDO = SM_PROG + 8;
constexpr uint32_t SM_VBAD = SM_PROG + 12;
constexpr uint32_t SMEM_BYTES = SM_PROG + 16 + 1024;

constexpr uint32_t PAGE = 2u << 20, CTL_STATE = 1536, CTL_PROBE = 2048;
__device__ __align__(1024) uint8_t g_scratch[(NGROUP / 2 + 1) * PAGE];
__device__ __forceinline__ uint32_t ring_off(int g, int t, int j) {
    const uint32_t s = t % RING, x = (j ^ (j >> 1) ^ (s >> 1) ^ g) & 1;
    return ((s * 4 + j) << 16) + (x ? 4096 : 12288);
}
__device__ __forceinline__ uint32_t ctl_off(int g) { return (g >> 1) * PAGE + ((g & 1) ? 53248 : 0); }

#define TR(ch, idx)
#define TP(ch, idx)
#define TRC(ch, idx)
#define TS(ch, idx)
#define TF(i)

constexpr uint32_t ST_OPEN = 0x80000000u, PAR_OPEN = 32;
constexpr unsigned long long TILE_READY = 0x0101010101010101ull;
constexpr uint32_t FLAG_VBAD = 0x04040404u;

__device__ __forceinline__ uint32_t smem_u32(const void* p) { return (uint32_t)__cvta_generic_to_shared(p); }
__device__ __forceinline__ void mbar_init(uint32_t bar, uint32_t cnt) {
    asm volatile("mbarrier.init.shared::cta.b64 [%0], %1;" ::"r"(bar), "r"(cnt) : "memory");
}
__device__ __forceinline__ void mbar_arrive(uint32_t bar) {
    asm volatile("mbarrier.arrive.shared::cta.b64 _, [%0];" ::"r"(bar) : "memory");
}
__device__ __forceinline__ void mbar_expect_tx(uint32_t bar, uint32_t bytes) {
    asm volatile("mbarrier.arrive.expect_tx.shared::cta.b64 _, [%0], %1;" ::"r"(bar), "r"(bytes) : "memory");
}
__device__ __forceinline__ void mbar_wait(uint32_t bar, uint32_t parity) {
    asm volatile("{\n.reg .pred p;\n.reg .u32 n;\n"
                 "mbarrier.try_wait.parity.shared::cta.b64 p, [%0], %1;\n@p bra DONE;\nmov.u32 n, 0;\n"
                 "LOOP:\nmbarrier.try_wait.parity.shared::cta.b64 p, [%0], %1;\n@p bra DONE;\n"
                 "add.u32 n, n, 1;\nsetp.lt.u32 p, n, %2;\n@p bra LOOP;\ntrap;\nDONE:\n}\n"
                 ::"r"(bar), "r"(parity), "n"(SPIN_LIMIT) : "memory");
}
__device__ __forceinline__ void mbar_wait_sleep(uint32_t bar, uint32_t parity) {
    asm volatile("{\n.reg .pred p;\n.reg .u32 n;\nmov.u32 n, 0;\n"
                 "LOOP:\nmbarrier.try_wait.parity.shared::cta.b64 p, [%0], %1, %3;\n@p bra DONE;\n"
                 "add.u32 n, n, 1;\nsetp.lt.u32 p, n, %2;\n@p bra LOOP;\ntrap;\nDONE:\n}\n"
                 ::"r"(bar), "r"(parity), "n"(1 << 18), "r"(10000) : "memory");
}
template <int N> __device__ __forceinline__ void bulk_load_mc(uint32_t dst, const void* src, uint32_t bar) {
    asm volatile("{\n.reg .pred p, q;\nelect.sync _|p, 0xffffffff;\nsetp.eq.and.u32 q, %5, 3, p;\n"
                 "@p mbarrier.arrive.expect_tx.shared::cta.b64 _, [%2], %4;\n"
                 "@p cp.async.bulk.shared::cluster.global.mbarrier::complete_tx::bytes.multicast::cluster [%0], [%1], 8192, [%2], %3;\n"
                 "@q cp.async.bulk.shared::cluster.global.mbarrier::complete_tx::bytes.multicast::cluster [%0 + 16384], [%1 + 16384], 8192, [%2], %3;\n"
                 "@q cp.async.bulk.shared::cluster.global.mbarrier::complete_tx::bytes.multicast::cluster [%0 + 32768], [%1 + 32768], 8192, [%2], %3;\n}\n"
                 ::"r"(dst), "l"(src), "r"(bar), "h"((uint16_t)((1 << CLUSTER) - 1)), "n"(N * SUB), "n"(N) : "memory");
}
__device__ __forceinline__ void tma_load_q16(uint32_t dst, const CUtensorMap* map, int g, uint32_t bar) {
    asm volatile("cp.async.bulk.tensor.4d.shared::cluster.global.mbarrier::complete_tx::bytes [%0], [%1, {%3, %3, %3, %4}], [%2];"
                 ::"r"(dst), "l"(map), "r"(bar), "r"(0), "r"(g) : "memory");
}
__device__ __forceinline__ void l2_prefetch(const void* p, uint32_t bytes) {
    asm volatile("{\n.reg .pred p;\nelect.sync _|p, 0xffffffff;\n@p cp.async.bulk.prefetch.L2.global [%0], %1;\n}\n" ::"l"(p), "r"(bytes) : "memory");
}
__device__ __forceinline__ uint64_t policy_evict_first() {
    uint64_t pol;
    asm volatile("createpolicy.fractional.L2::evict_first.b64 %0, 1.0;" : "=l"(pol));
    return pol;
}
__device__ __forceinline__ void wg_fence() { asm volatile("wgmma.fence.sync.aligned;" ::: "memory"); }
__device__ __forceinline__ void wg_commit() { asm volatile("wgmma.commit_group.sync.aligned;" ::: "memory"); }
template <int N> __device__ __forceinline__ void wg_wait() { asm volatile("wgmma.wait_group.sync.aligned %0;" ::"n"(N) : "memory"); }
__device__ __forceinline__ void bar_sync(int id) { asm volatile("bar.sync %0, 256;" ::"r"(id) : "memory"); }
__device__ __forceinline__ void bar_arrive(int id) { asm volatile("bar.arrive %0, 256;" ::"r"(id) : "memory"); }
__device__ __forceinline__ float ex2(float x) { float y; asm("ex2.approx.ftz.f32 %0, %1;" : "=f"(y) : "f"(x)); return y; }
__device__ __forceinline__ float rcp(float x) { float y; asm volatile("rcp.approx.ftz.f32 %0, %1;" : "=f"(y) : "f"(x)); return y; }
__device__ __forceinline__ uint32_t pack_bf16(float lo, float hi) {
    uint32_t r; asm("cvt.rn.bf16x2.f32 %0, %1, %2;" : "=r"(r) : "f"(hi), "f"(lo)); return r;
}
__device__ __forceinline__ uint32_t bf2_add(uint32_t a, uint32_t b) { uint32_t r; asm("add.rn.bf16x2 %0, %1, %2;" : "=r"(r) : "r"(a), "r"(b)); return r; }
__device__ __forceinline__ uint32_t bf2_sub(uint32_t a, uint32_t b) { uint32_t r; asm("sub.rn.bf16x2 %0, %1, %2;" : "=r"(r) : "r"(a), "r"(b)); return r; }
__device__ __forceinline__ uint32_t bf2_mul(uint32_t a, uint32_t b) { uint32_t r; asm("mul.rn.bf16x2 %0, %1, %2;" : "=r"(r) : "r"(a), "r"(b)); return r; }
__device__ __forceinline__ uint32_t bf2_fma(uint32_t a, uint32_t b, uint32_t c) { uint32_t r; asm("fma.rn.bf16x2 %0, %1, %2, %3;" : "=r"(r) : "r"(a), "r"(b), "r"(c)); return r; }
__device__ __forceinline__ float bf_lo(uint32_t w) { return __uint_as_float(w << 16); }
__device__ __forceinline__ float bf_hi(uint32_t w) { return __uint_as_float(w & 0xffff0000u); }
__device__ __forceinline__ int4 ldg_stream(const void* p, uint64_t pol) {
    int4 v;
    asm volatile("ld.global.nc.L1::no_allocate.L2::cache_hint.v4.s32 {%0,%1,%2,%3}, [%4], %5;"
                 : "=r"(v.x), "=r"(v.y), "=r"(v.z), "=r"(v.w) : "l"(p), "l"(pol));
    return v;
}
__device__ __forceinline__ uint4 lds_v4(uint32_t a) {
    uint4 v;
    asm volatile("ld.shared.v4.u32 {%0,%1,%2,%3}, [%4];" : "=r"(v.x), "=r"(v.y), "=r"(v.z), "=r"(v.w) : "r"(a) : "memory");
    return v;
}
__device__ __forceinline__ uint32_t lds_u32(uint32_t a) { uint32_t v; asm volatile("ld.shared.u32 %0, [%1];" : "=r"(v) : "r"(a) : "memory"); return v; }
template <int R> __device__ __forceinline__ void fence_regs(float (&d)[R]) {
#pragma unroll
    for (int i = 0; i < R; i++) asm volatile("" : "+f"(d[i])::"memory");
}
template <int R> __device__ __forceinline__ void fence_regs(uint32_t (&d)[R]) {
#pragma unroll
    for (int i = 0; i < R; i++) asm volatile("" : "+r"(d[i])::"memory");
}
template <bool B> struct Flag { static constexpr bool value = B; };

__device__ __forceinline__ void wgmma_ss_n128(float (&d)[64], uint32_t alo, uint32_t blo, int scale_d) {
    asm volatile(
        "{\n.reg .pred p;\n.reg .b64 da, db;\nsetp.ne.b32 p, %66, 0;\nmov.b64 da, {%64, 0x400000C0};\nmov.b64 db, {%65, 0x40000040};\n"
        "wgmma.mma_async.sync.aligned.m64n128k16.f32.bf16.bf16 "
        "{%0, %1, %2, %3, %4, %5, %6, %7, %8, %9, %10, %11, %12, %13, %14, %15, "
        "%16, %17, %18, %19, %20, %21, %22, %23, %24, %25, %26, %27, %28, %29, %30, %31, "
        "%32, %33, %34, %35, %36, %37, %38, %39, %40, %41, %42, %43, %44, %45, %46, %47, "
        "%48, %49, %50, %51, %52, %53, %54, %55, %56, %57, %58, %59, %60, %61, %62, %63}, "
        "da, db, p, 1, 1, 0, 0;\n}\n"
        :
          "+f"(d[0]), "+f"(d[1]), "+f"(d[2]), "+f"(d[3]), "+f"(d[4]), "+f"(d[5]), "+f"(d[6]), "+f"(d[7]),
          "+f"(d[8]), "+f"(d[9]), "+f"(d[10]), "+f"(d[11]), "+f"(d[12]), "+f"(d[13]), "+f"(d[14]), "+f"(d[15]),
          "+f"(d[16]), "+f"(d[17]), "+f"(d[18]), "+f"(d[19]), "+f"(d[20]), "+f"(d[21]), "+f"(d[22]), "+f"(d[23]),
          "+f"(d[24]), "+f"(d[25]), "+f"(d[26]), "+f"(d[27]), "+f"(d[28]), "+f"(d[29]), "+f"(d[30]), "+f"(d[31]),
          "+f"(d[32]), "+f"(d[33]), "+f"(d[34]), "+f"(d[35]), "+f"(d[36]), "+f"(d[37]), "+f"(d[38]), "+f"(d[39]),
          "+f"(d[40]), "+f"(d[41]), "+f"(d[42]), "+f"(d[43]), "+f"(d[44]), "+f"(d[45]), "+f"(d[46]), "+f"(d[47]),
          "+f"(d[48]), "+f"(d[49]), "+f"(d[50]), "+f"(d[51]), "+f"(d[52]), "+f"(d[53]), "+f"(d[54]), "+f"(d[55]),
          "+f"(d[56]), "+f"(d[57]), "+f"(d[58]), "+f"(d[59]), "+f"(d[60]), "+f"(d[61]), "+f"(d[62]), "+f"(d[63])
        : "r"(alo), "r"(blo), "r"(scale_d));
}

__device__ __forceinline__ void wgmma_rs_n192_tb(float (&d)[96], uint32_t a0, uint32_t a1, uint32_t a2, uint32_t a3, uint32_t blo, int scale_d) {
    asm volatile(
        "{\n.reg .pred p;\n.reg .b64 db;\nsetp.ne.b32 p, %101, 0;\nmov.b64 db, {%100, 0x40000040};\n"
        "wgmma.mma_async.sync.aligned.m64n192k16.f32.bf16.bf16 "
        "{%0, %1, %2, %3, %4, %5, %6, %7, %8, %9, %10, %11, %12, %13, %14, %15, "
        "%16, %17, %18, %19, %20, %21, %22, %23, %24, %25, %26, %27, %28, %29, %30, %31, "
        "%32, %33, %34, %35, %36, %37, %38, %39, %40, %41, %42, %43, %44, %45, %46, %47, "
        "%48, %49, %50, %51, %52, %53, %54, %55, %56, %57, %58, %59, %60, %61, %62, %63, "
        "%64, %65, %66, %67, %68, %69, %70, %71, %72, %73, %74, %75, %76, %77, %78, %79, "
        "%80, %81, %82, %83, %84, %85, %86, %87, %88, %89, %90, %91, %92, %93, %94, %95}, "
        "{%96, %97, %98, %99}, db, p, 1, 1, 1;\n}\n"
        :
          "+f"(d[0]), "+f"(d[1]), "+f"(d[2]), "+f"(d[3]), "+f"(d[4]), "+f"(d[5]), "+f"(d[6]), "+f"(d[7]),
          "+f"(d[8]), "+f"(d[9]), "+f"(d[10]), "+f"(d[11]), "+f"(d[12]), "+f"(d[13]), "+f"(d[14]), "+f"(d[15]),
          "+f"(d[16]), "+f"(d[17]), "+f"(d[18]), "+f"(d[19]), "+f"(d[20]), "+f"(d[21]), "+f"(d[22]), "+f"(d[23]),
          "+f"(d[24]), "+f"(d[25]), "+f"(d[26]), "+f"(d[27]), "+f"(d[28]), "+f"(d[29]), "+f"(d[30]), "+f"(d[31]),
          "+f"(d[32]), "+f"(d[33]), "+f"(d[34]), "+f"(d[35]), "+f"(d[36]), "+f"(d[37]), "+f"(d[38]), "+f"(d[39]),
          "+f"(d[40]), "+f"(d[41]), "+f"(d[42]), "+f"(d[43]), "+f"(d[44]), "+f"(d[45]), "+f"(d[46]), "+f"(d[47]),
          "+f"(d[48]), "+f"(d[49]), "+f"(d[50]), "+f"(d[51]), "+f"(d[52]), "+f"(d[53]), "+f"(d[54]), "+f"(d[55]),
          "+f"(d[56]), "+f"(d[57]), "+f"(d[58]), "+f"(d[59]), "+f"(d[60]), "+f"(d[61]), "+f"(d[62]), "+f"(d[63]),
          "+f"(d[64]), "+f"(d[65]), "+f"(d[66]), "+f"(d[67]), "+f"(d[68]), "+f"(d[69]), "+f"(d[70]), "+f"(d[71]),
          "+f"(d[72]), "+f"(d[73]), "+f"(d[74]), "+f"(d[75]), "+f"(d[76]), "+f"(d[77]), "+f"(d[78]), "+f"(d[79]),
          "+f"(d[80]), "+f"(d[81]), "+f"(d[82]), "+f"(d[83]), "+f"(d[84]), "+f"(d[85]), "+f"(d[86]), "+f"(d[87]),
          "+f"(d[88]), "+f"(d[89]), "+f"(d[90]), "+f"(d[91]), "+f"(d[92]), "+f"(d[93]), "+f"(d[94]), "+f"(d[95])
        : "r"(a0), "r"(a1), "r"(a2), "r"(a3), "r"(blo), "r"(scale_d));
}

struct Params {
    const int* qk; const int* qv;
    const __nv_bfloat16* ks; const __nv_bfloat16* kz; const __nv_bfloat16* vs; const __nv_bfloat16* vz;
    const __nv_bfloat16* q; __nv_bfloat16* out;
    uint8_t* pages;
    uint32_t zero;
};

constexpr float SCALE = 0.07216878364870322f * 1.4426950408889634f;
constexpr uint32_t VSCALE2 = 0x3f80u | ((uint32_t)(127 + VEXP) << 23);
__device__ __forceinline__ void set_flag(uint32_t flag) { asm volatile("st.shared.u8 [%0], %1;" ::"r"(flag), "r"(2) : "memory"); }
constexpr float QNORM2 = 14.f;
__device__ __forceinline__ void sq_acc(uint32_t (&x)[4], uint4 v) {
    x[0] = bf2_fma(v.x, v.x, x[0]); x[1] = bf2_fma(v.y, v.y, x[1]); x[2] = bf2_fma(v.z, v.z, x[2]); x[3] = bf2_fma(v.w, v.w, x[3]);
}
__device__ __forceinline__ float sq_sum(const uint32_t (&x)[4]) {
    const uint32_t y = bf2_add(bf2_add(x[0], x[1]), bf2_add(x[2], x[3]));
    return bf_lo(y) + bf_hi(y);
}
__device__ __forceinline__ bool q8_big(uint32_t rows) {
    uint32_t lane;
    asm volatile("mov.u32 %0, %laneid;" : "=r"(lane));
    uint32_t x[4] = {0, 0, 0, 0}, y[4] = {0, 0, 0, 0};
#pragma unroll
    for (int a = 0; a < 3; a++) { sq_acc(x, lds_v4(rows + lane * 16 + a * 1024)); sq_acc(y, lds_v4(rows + lane * 16 + a * 1024 + 512)); }
    float f = sq_sum(x), g = sq_sum(y);
#pragma unroll
    for (int m = 1; m < 8; m *= 2) { f += __shfl_xor_sync(0xffffffffu, f, m); g += __shfl_xor_sync(0xffffffffu, g, m); }
    return !(f <= QNORM2 && g <= QNORM2);
}

struct KScale {
    float s0, s1, s2, s3, n0, n1, n2, n3;
    __device__ __forceinline__ KScale(uint2 sc, uint2 z, float c) {
        s0 = bf_lo(sc.x) * SCALE; s1 = bf_hi(sc.x) * SCALE; s2 = bf_lo(sc.y) * SCALE; s3 = bf_hi(sc.y) * SCALE;
        n0 = fmaf(-bf_lo(z.x), s0, c); n1 = fmaf(-bf_hi(z.x), s1, c); n2 = fmaf(-bf_lo(z.y), s2, c); n3 = fmaf(-bf_hi(z.y), s3, c);
    }
    __device__ __forceinline__ uint2 operator()(int4 v) const {
        return make_uint2(pack_bf16(fmaf((float)v.x, s0, n0), fmaf((float)v.y, s1, n1)),
                          pack_bf16(fmaf((float)v.z, s2, n2), fmaf((float)v.w, s3, n3)));
    }
};
template <bool CHECK>
__device__ __forceinline__ uint32_t deq_v4(int4 v, uint32_t zs, uint32_t off, uint8_t* d0, uint8_t* d1) {
    const uint32_t z = __byte_perm(zs, 0, 0x1010), sc = __byte_perm(zs, 0, 0x3232);
    const uint32_t a = bf2_mul(bf2_sub(pack_bf16((float)v.x, (float)v.y), z), sc);
    const uint32_t b = bf2_mul(bf2_sub(pack_bf16((float)v.z, (float)v.w), z), sc);
    *(uint32_t*)d0 = bf2_add(a, off);
    *(uint32_t*)d1 = bf2_add(b, off);
    uint32_t far = 0;
    if (CHECK)
        asm("{\n.reg .b32 x, y, t;\nabs.bf16x2 x, %1;\nabs.bf16x2 y, %2;\nmax.bf16x2 x, x, y;\nmul.rn.bf16x2 t, %3, %4;\n"
            "set.ge.u32.bf16x2 %0, x, t;\n}\n" : "=r"(far) : "r"(a), "r"(b), "r"(off), "r"(0x3e803e80u));
    return far;
}
__device__ __forceinline__ uint32_t v_offset(const Params& P, int head, int lane) {
    float w = __bfloat162float(__ldg(P.vs + (size_t)head * SEQ + lane)) * __bfloat162float(__ldg(P.vz + (size_t)head * SEQ + lane));
#pragma unroll
    for (int m = 16; m >= 1; m >>= 1) w += __shfl_xor_sync(0xffffffffu, w, m);
    w = fmaxf(w * (VOFF / 32.f * __uint_as_float((127 + VEXP) << 23)), 0.f);
    return pack_bf16(w, w);
}
__device__ __forceinline__ void put_v_offset(uint32_t entry, uint32_t off) {
    asm volatile("st.shared.v2.b32 [%0 + 8], {%1, %2};" ::"r"(entry), "r"(off), "r"(__float_as_uint(-bf_lo(off) * __uint_as_float((127 - VEXP) << 23))) : "memory");
}
__device__ __forceinline__ void set_vbad(uint32_t flag) { asm volatile("st.shared.u8 [%0], %1;" ::"r"(flag), "r"(4) : "memory"); }
__device__ __forceinline__ uint32_t load_vzs(const Params& P, size_t idx) {
    return bf2_mul((uint32_t)__bfloat16_as_ushort(__ldg(P.vz + idx)) | ((uint32_t)__bfloat16_as_ushort(__ldg(P.vs + idx)) << 16), VSCALE2);
}
__device__ __forceinline__ void part_k(const Params& P, const uint8_t* src, const uint8_t* sp, const uint8_t* zp, uint8_t* slot, uint32_t doff, uint64_t pol,
                                       uint32_t koff) {
    int4 v[4];
    uint2 sc = __ldg((const uint2*)sp);
    const uint2 z = __ldg((const uint2*)zp);
#pragma unroll
    for (int a = 0; a < 4; a++) v[a] = ldg_stream(src + (a & 1) * 1536 + (a >> 1) * 6144, pol);
    uint32_t lo[4], hi[4];
    const float c = __uint_as_float(lds_u32(koff));
    {
        sc.x ^= v[3].w & P.zero;
        const float s0 = bf_lo(sc.x) * SCALE, s1 = bf_hi(sc.x) * SCALE, n0 = fmaf(-bf_lo(z.x), s0, c), n1 = fmaf(-bf_hi(z.x), s1, c);
#pragma unroll
        for (int a = 0; a < 4; a++) lo[a] = pack_bf16(fmaf((float)v[a].x, s0, n0), fmaf((float)v[a].y, s1, n1));
    }
    {
        sc.y ^= lo[3] & P.zero;
        const float s0 = bf_lo(sc.y) * SCALE, s1 = bf_hi(sc.y) * SCALE, n0 = fmaf(-bf_lo(z.y), s0, c), n1 = fmaf(-bf_hi(z.y), s1, c);
#pragma unroll
        for (int a = 0; a < 4; a++) hi[a] = pack_bf16(fmaf((float)v[a].z, s0, n0), fmaf((float)v[a].w, s1, n1));
    }
    doff ^= lo[3] & P.zero;
#pragma unroll
    for (int a = 0; a < 4; a++) *(uint2*)(slot + ((a & 1) ? (doff ^ 32) + 256 : doff) + (a >> 1) * 1024) = make_uint2(lo[a], hi[a]);
}
template <bool CHECK>
__device__ __forceinline__ bool part_v(const Params& P, const uint8_t* src, size_t key0, int h, uint8_t* slot, uint32_t doff, uint64_t pol, uint32_t voff) {
    int4 v[4];
#pragma unroll
    for (int a = 0; a < 4; a++) v[a] = ldg_stream(src + (a & 1) * 1536 + (a >> 1) * 6144, pol);
    uint32_t ln;
    asm volatile("mov.u32 %0, %laneid;" : "=r"(ln));
    const uint32_t zs = load_vzs(P, key0 + (ln & 15));
    int r0 = 4 * h + (ln >> 4);
    r0 ^= v[3].w & P.zero;
    doff ^= v[3].w & P.zero;
    uint8_t* d0 = slot + doff; uint8_t* d1 = slot + (doff ^ 32);
    const uint32_t off = lds_u32(voff);
    uint32_t m = 0;
#pragma unroll
    for (int a = 0; a < 4; a++) {
        const int o = (a & 1) * 256 + (a >> 1) * 1024;
        m |= deq_v4<CHECK>(v[a], __shfl_sync(0xffffffffu, zs, r0 + (a & 1) * 2 + (a >> 1) * 8), off, ((a & 1) ? d1 : d0) + o, ((a & 1) ? d0 : d1) + o) & (0x00010001u << a);
    }
    if (!CHECK) return true;
    m = ((m | m >> 16) & 15) << (r0 & 1) * 4;
    return __reduce_or_sync(0xffffffffu, m) == 255;
}
__device__ __forceinline__ void start_k(const Params& P, int head, int key0, uint8_t* img, int w, int lane, uint64_t pol, float koff) {
    const int hw = lane >> 4, l16 = lane & 15;
    const uint8_t* src = (const uint8_t*)(P.qk + ((size_t)head * SEQ + key0) * DH) + (uint32_t)(w * 3072 + hw * 768 + l16 * 16);
    const size_t so = ((size_t)head * 32 + (key0 >> 6)) * DH + l16 * 4;
    int4 v[3][2]; uint2 z[3], sc[3];
#pragma unroll
    for (int c = 0; c < 3; c++) {
        v[c][0] = ldg_stream(src + c * 256, pol); v[c][1] = ldg_stream(src + 1536 + c * 256, pol);
        z[c] = __ldg((const uint2*)(P.kz + so + c * 64)); sc[c] = __ldg((const uint2*)(P.ks + so + c * 64));
    }
#pragma unroll
    for (int c = 0; c < 3; c++) {
        const KScale f(sc[c], z[c], koff);
#pragma unroll
        for (int a = 0; a < 2; a++) {
            const int row = (key0 & 127) + 4 * w + 2 * a + hw;
            *(uint2*)(img + c * SUB + row * 128 + (((l16 >> 1) ^ (row & 7)) << 4) + (l16 & 1) * 8) = f(v[c][a]);
        }
    }
}
template <bool OFFSET>
__device__ __forceinline__ bool start_v(const Params& P, int head, int key0, uint8_t* img, int w, int lane, uint64_t pol) {
    const int hw = lane >> 4, l16 = lane & 15, g = (l16 >> 3) * 4 + (l16 & 1);
    const uint8_t* src = (const uint8_t*)(P.qv + ((size_t)head * SEQ + key0) * DH) + (uint32_t)(w * 1536 + hw * 768 + l16 * 16);
    int4 v[3];
#pragma unroll
    for (int c = 0; c < 3; c++) v[c] = ldg_stream(src + c * 256, pol);
    const uint32_t zs = load_vzs(P, (size_t)head * SEQ + key0 + 2 * w + hw);
    const uint32_t off = OFFSET ? v_offset(P, head, lane) : 0;
    const int row = (key0 & 127) + 2 * w + hw;
    uint32_t far = 0;
#pragma unroll
    for (int c = 0; c < 3; c++) {
        uint8_t* d = img + c * SUB + row * 128 + ((l16 >> 1) & 3) * 4;
        far |= deq_v4<OFFSET>(v[c], zs, off, d + ((g ^ (row & 7)) << 4), d + ((g ^ 2 ^ (row & 7)) << 4));
    }
    if (!OFFSET) return true;
    const uint32_t b = __ballot_sync(0xffffffffu, far != 0);
    return (b & 0xffff) && (b >> 16);
}

__device__ __forceinline__ void proxy_fence_global() { asm volatile("fence.proxy.async.global;" ::: "memory"); }
__device__ __forceinline__ void publish(unsigned long long* flag, int byte, uint32_t val) {
    proxy_fence_global();
    asm volatile("st.release.gpu.global.u8 [%0], %1;" ::"l"((uint8_t*)flag + byte), "r"(val) : "memory");
}
__device__ __forceinline__ void wait_flag(const unsigned long long* f, uint32_t redo) {
    uint32_t n = 0;
    while (true) {
        unsigned long long v;
        asm volatile("ld.acquire.gpu.global.u64 %0, [%1];" : "=l"(v) : "l"(f) : "memory");
        if (__all_sync(0xffffffffu, (v & TILE_READY) == TILE_READY)) {
            if (redo && (((uint32_t)v | (uint32_t)(v >> 32)) & FLAG_VBAD)) set_flag(redo);
            __syncwarp();
            break;
        }
        if (++n > SPIN_LIMIT) __trap();
        __nanosleep(20);
    }
}
__device__ __forceinline__ void wait_flags(const unsigned long long* f, uint32_t skip, uint32_t koff, uint32_t redo) {
    constexpr uint32_t READY = (uint32_t)TILE_READY;
    uint32_t n = 0;
    while (true) {
        uint32_t a, b, c, d;
        asm volatile("ld.acquire.gpu.global.v4.u32 {%0, %1, %2, %3}, [%4];" : "=r"(a), "=r"(b), "=r"(c), "=r"(d) : "l"(f) : "memory");
        if (__all_sync(0xffffffffu, (a & b & ((c & d) | skip) & READY) == READY)) {
            if ((a | b | c | d) != READY) {
                if (koff) asm volatile("st.shared.v4.u32 [%0], {%1, %1, %1, %1};" ::"r"(koff), "r"(0) : "memory");
                if ((c | d) & ~skip & FLAG_VBAD) set_flag(redo);
            }
            __syncwarp();
            break;
        }
        if (++n > SPIN_LIMIT) __trap();
        __nanosleep(20);
    }
}
__device__ __forceinline__ uint32_t atom_add0(const void* p, uint32_t x) {
    uint32_t v;
    asm volatile("{\n.reg .pred p;\n.reg .u32 l;\nmov.u32 l, %laneid;\nsetp.eq.u32 p, l, 0;\nmov.u32 %0, 0;\n"
                 "@p atom.relaxed.gpu.global.add.u32 %0, [%1], %2;\n}\n" : "=r"(v) : "l"(p), "r"(x) : "memory");
    return v;
}
__device__ __forceinline__ uint32_t clock_after(uint32_t v) {
    uint32_t c;
    asm volatile("{\n.reg .u32 t;\nshfl.sync.idx.b32 t, %1, 0, 31, 0xffffffff;\nmov.u32 %0, %clock;\nadd.u32 %0, %0, t;\n}\n" : "=r"(c) : "r"(v) : "memory");
    return c;
}
__device__ __forceinline__ void wait_until(uint32_t c0, uint32_t clks) {
    while (__shfl_sync(0xffffffffu, (uint32_t)clock() - c0, 0) < clks) __nanosleep(32);
}
__device__ __forceinline__ void cluster_arrive() { asm volatile("barrier.cluster.arrive.relaxed.aligned;" ::: "memory"); }
__device__ __forceinline__ void cluster_wait() { asm volatile("barrier.cluster.wait.acquire.aligned;" ::: "memory"); }

struct Softmax {
    float m0, m1, l0, l1, a0, a1;
    bool fast, resc;

    template <bool first> __device__ __forceinline__ void run(float (&s)[64]) {
        if (first) { l0 = 0.f; l1 = 0.f; }
        if (fast) {
            resc = false;
#pragma unroll
            for (int j = 0; j < 64; j++) s[j] = ex2(s[j]);
            float x0 = s[0], x1 = s[2], y0 = s[1], y1 = s[3];
#pragma unroll
            for (int j = 1; j < 16; j++) { x0 += s[4 * j]; y0 += s[4 * j + 1]; x1 += s[4 * j + 2]; y1 += s[4 * j + 3]; }
            l0 += x0 + y0; l1 += x1 + y1;
        } else {
            float x0 = fmaxf(s[0], s[1]), x1 = fmaxf(s[2], s[3]), y0 = fmaxf(s[4], s[5]), y1 = fmaxf(s[6], s[7]);
#pragma unroll
            for (int j = 2; j < 16; j += 2) {
                x0 = fmaxf(x0, fmaxf(s[4 * j], s[4 * j + 1]));     x1 = fmaxf(x1, fmaxf(s[4 * j + 2], s[4 * j + 3]));
                y0 = fmaxf(y0, fmaxf(s[4 * j + 4], s[4 * j + 5])); y1 = fmaxf(y1, fmaxf(s[4 * j + 6], s[4 * j + 7]));
            }
            x0 = fmaxf(x0, y0); x1 = fmaxf(x1, y1);
            x0 = fmaxf(x0, __shfl_xor_sync(0xffffffffu, x0, 1));
            x1 = fmaxf(x1, __shfl_xor_sync(0xffffffffu, x1, 1));
            x0 = fmaxf(x0, __shfl_xor_sync(0xffffffffu, x0, 2));
            x1 = fmaxf(x1, __shfl_xor_sync(0xffffffffu, x1, 2));
            if (first) {
                a0 = 0.f; a1 = 0.f;
                resc = false;
            } else {
                x0 = fmaxf(x0, m0); x1 = fmaxf(x1, m1);
                a0 = ex2(m0 - x0); a1 = ex2(m1 - x1);
                resc = __any_sync(0xffffffffu, x0 != m0 || x1 != m1);
            }
            m0 = x0; m1 = x1;
            float r0 = 0.f, r1 = 0.f;
#pragma unroll
            for (int j = 0; j < 16; j++) {
                s[4 * j] = ex2(s[4 * j] - x0); s[4 * j + 1] = ex2(s[4 * j + 1] - x0);
                s[4 * j + 2] = ex2(s[4 * j + 2] - x1); s[4 * j + 3] = ex2(s[4 * j + 3] - x1);
                r0 += s[4 * j] + s[4 * j + 1];
                r1 += s[4 * j + 2] + s[4 * j + 3];
            }
            l0 = fmaf(l0, a0, r0); l1 = fmaf(l1, a1, r1);
        }
    }
    __device__ __forceinline__ void pack(const float (&s)[64], uint32_t (&p)[32]) {
#pragma unroll
        for (int j = 0; j < 32; j++) p[j] = pack_bf16(s[2 * j], s[2 * j + 1]);
    }
    __device__ __forceinline__ void rescale(float (&o)[96]) {
        if (resc) {
#pragma unroll
            for (int i = 0; i < 24; i++) { o[4 * i] *= a0; o[4 * i + 1] *= a0; o[4 * i + 2] *= a1; o[4 * i + 3] *= a1; }
        }
    }
    __device__ __forceinline__ void finish(float& i0, float& i1, uint32_t redo) {
        float f0 = l0 + __shfl_xor_sync(0xffffffffu, l0, 1), f1 = l1 + __shfl_xor_sync(0xffffffffu, l1, 1);
        f0 += __shfl_xor_sync(0xffffffffu, f0, 2); f1 += __shfl_xor_sync(0xffffffffu, f1, 2);
        i0 = rcp(f0 * __uint_as_float((127 + VEXP) << 23)); i1 = rcp(f1 * __uint_as_float((127 + VEXP) << 23));
        constexpr uint32_t lo = (127 - 40) << 23, span = 80 << 23;
        if (__any_sync(0xffffffffu, __float_as_uint(f0) - lo > span || __float_as_uint(f1) - lo > span)) { fast = false; set_flag(redo); }
    }
};
__device__ __forceinline__ void q_first(const CUtensorMap* qmap, uint32_t dst, int row0, uint32_t bar) {
#pragma unroll
    for (int w = 0; w < 4; w++) { mbar_expect_tx(bar, 6144); tma_load_q16(dst + w * 6144, qmap, (row0 >> 3) + 2 * w, bar); }
}

__global__ void __cluster_dims__(CLUSTER, 1, 1) __launch_bounds__(512, 1)
kvq_attn_kernel(const __grid_constant__ Params P, const __grid_constant__ CUtensorMap qmap) {
    extern __shared__ uint8_t smem_raw[];
    const uint32_t sb = (smem_u32(smem_raw) + 1023) & ~1023u;
    const int tid = threadIdx.x;
    if (tid == 128) {
        const uint32_t b = blockIdx.x;
        const uint8_t* src = *(const uint8_t* const*)((const uint8_t*)&P.qk + (b & 8)) + ((b >> 4) * (SEQ / 16) + (b & 7)) * (16 * DH * 4);
        asm volatile("{\n.reg .pred p;\nsetp.eq.u32 p, %1, 0;\ncp.async.bulk.prefetch.L2.global [%0], 12288;\n"
                     "@p cp.async.bulk.prefetch.L2.global [%0 + 98304], 12288;\n}\n" ::"l"(src), "r"(b & 8) : "memory");
    }
    const int warp = __shfl_sync(0xffffffffu, tid >> 5, 0), wg = warp >> 2;
    const uint32_t clk0 = (uint32_t)clock();
    auto role = [&]() { mbar_wait_sleep(sb + B_ROLE, 0); return __shfl_sync(0xffffffffu, lds_u32(sb + SM_ROLE), 0); };

    if (tid == 160) { TS(0, 70); }
    if (wg == 0 || wg == 3) {
        const int lane = tid & 31;
        const uint32_t crank = blockIdx.x % CLUSTER;
        uint32_t* state = (uint32_t*)(P.pages + CTL_STATE);
        uint8_t* probe = P.pages + ctl_off(warp & 7) + CTL_PROBE + (blockIdx.x >> 1) * 32;
        uint32_t v0 = 0;
        if (crank == 0) {
            asm volatile("{\n.reg .pred p;\nsetp.lt.u32 p, %2, 2;\n@p st.global.v4.u32 [%0], {%1, %1, %1, %1};\n}\n"
                         ::"l"(probe + lane * 16), "r"(0), "r"(lane) : "memory");
            v0 = atom_add0(probe, 0);
        } else if (warp > 3) {
            const uint32_t n = warp & 2 ? 512 : 1536;
            l2_prefetch((const uint8_t*)(&P.ks)[warp & 3] + (blockIdx.x >> 1) * n, n);
        } else {
            asm volatile("{\n.reg .pred p;\nsetp.eq.u32 p, %4, 0;\n@p st.relaxed.gpu.global.v4.u32 [%0], {%1, %2, %3, %3};\n}\n"
                         ::"l"(state + (lane & 1) * 4), "r"(ST_OPEN), "r"(PAR_OPEN), "r"(0), "r"(((tid ^ 64) | blockIdx.x) >> 1) : "memory");
        }
        if (tid == 0) {
            asm volatile("prefetch.tensormap [%0];" ::"l"(&qmap) : "memory");
            for (int i = 0; i < KSLOTS; i++) { mbar_init(sb + B_KFULL + 8 * i, 1); mbar_init(sb + B_KEMPTY + 8 * i, 2 * CLUSTER); }
            for (int i = 0; i < 2; i++) {
                mbar_init(sb + B_VFULL + 8 * i, 1); mbar_init(sb + B_VEMPTY + 8 * i, 2 * CLUSTER);
                mbar_init(sb + B_QFULL + 8 * i, 4);
            }
            for (int i = 0; i < 8; i++) mbar_init(sb + B_UNIT + 8 * i, 6);
            mbar_init(sb + B_ROLE, 1); mbar_expect_tx(sb + B_ROLE, 4);
            for (int i = 0; i < 4; i++) asm volatile("st.shared.v4.f32 [%0], {%1, %2, %2, %2};" ::"r"(sb + SM_OFF + 16 * i), "f"(KOFF), "f"(0.f) : "memory");
            asm volatile("st.shared.v4.u32 [%0], {%1, %2, %2, %2};" ::"r"(sb + SM_PROG), "r"(-64), "r"(0) : "memory");
            asm volatile("fence.acq_rel.cta;" ::: "memory");
            asm volatile("fence.mbarrier_init.release.cluster;" ::: "memory");
            asm volatile("fence.proxy.async.shared::cta;" ::: "memory");
        }
        __syncwarp();
        cluster_arrive();
        asm volatile("setmaxnreg.dec.sync.aligned.u32 32;");
        auto pf_scales = [&](int item, int id) {
            const size_t h = item * NGROUP + (id >> 4);
            const int r = id & 15;
            l2_prefetch(P.ks + h * 32 * DH + r * 384, 768); l2_prefetch(P.kz + h * 32 * DH + r * 384, 768);
            l2_prefetch(P.vs + h * SEQ + r * 128, 256);     l2_prefetch(P.vz + h * SEQ + r * 128, 256);
        };
        if (crank == 0) {
            asm volatile("bar.sync 5, %0;" ::"r"(256 + __shfl_sync(0xffffffffu, v0, 0)) : "memory");
            const uint32_t c0 = clock_after(v0);
            const uint32_t c1 = clock_after(atom_add0(probe, 0));
            asm volatile("st.shared.u32 [%0], %1;" ::"r"(sb + SM_LAT + (warp & 7) * 4), "r"(c1 - c0) : "memory");
            cluster_wait();
            if (warp != 1) bar_arrive(4);
            else {
                bar_sync(4);
                uint2 a;
                asm volatile("ld.shared.v2.u32 {%0,%1}, [%2];" : "=r"(a.x), "=r"(a.y) : "r"(sb + SM_LAT + (lane & 3) * 8) : "memory");
                uint32_t par = __ballot_sync(0xffffffffu, a.x > a.y) & 15, par0 = 0;
                const uint32_t side = par & 1;
                par = (par ^ (side * 15)) | 16;
                uint32_t n = 0;
#pragma unroll 1
                for (int i = 0; !(n & ST_OPEN) || !par0; i++) {
                    if (i >> 16) __trap();
                    asm volatile("{\n.reg .pred p, q;\nsetp.eq.u32 p, %5, 0;\nsetp.ge.and.s32 q, %0, 0, p;\n"
                                 "@p atom.relaxed.gpu.global.cas.b32 %1, [%2 + 4], %6, %4;\n"
                                 "@q atom.relaxed.gpu.global.add.u32 %0, [%2], %3;\n}\n"
                                 : "+r"(n), "+r"(par0) : "l"(state), "r"(side ? 256 : 1), "r"(par), "r"(lane), "n"(PAR_OPEN) : "memory");
                    n = __shfl_sync(0xffffffffu, n, 0); par0 = __shfl_sync(0xffffffffu, par0, 0);
                }
                if (par0 != PAR_OPEN) par = par0;
                n = side ? 63 - (n >> 8 & 255) : n & 255;
                const uint32_t up = n >> 5, k = up ? 63 - n : n;
                const uint32_t id = (((k >> 3) * 2 + ((par >> (k >> 3) & 1) ^ up)) * 8 + (k & 7)) * CLUSTER;
                asm volatile("{\n.reg .u32 a;\n.reg .pred p;\nsetp.lt.u32 p, %1, 2;\nmapa.shared::cluster.u32 a, %0, %3;\n"
                             "@p st.async.weak.shared::cluster.mbarrier::complete_tx::bytes.u32 [a + 8], %2, [a];\n}\n"
                             ::"r"(sb + B_ROLE), "r"(lane), "r"(id + lane), "r"(lane & 1) : "memory");
            }
        } else {
#pragma unroll 1
            for (int i = 0; i < (warp == 3 ? 12 : 0); i++) {
                wait_until(clk0, Q_T0 + i * Q_DT);
                l2_prefetch(P.q + (size_t)((blockIdx.x - (i & 1)) * 128 * DH + (i >> 1) * 4096), 8192);
            }
            cluster_wait();
        }
        const int bid = role(), grp = bid >> 4, rk = bid & 15;
        uint8_t* ring = P.pages + (grp >> 1) * PAGE;
        unsigned long long* flags = (unsigned long long*)(P.pages + ctl_off(grp));
        if (warp == 0) {
            wait_until(clk0, POLL_T);
            __syncwarp();
            constexpr int VSEP = 8;
            uint32_t kslot = 0, kphase = 1;
            auto load_k = [&](int t, int c) {
                if (t >= TOTAL) return;
                if (c == 0) {
                    if (t > 1) { TP(5, t); }
                    if (t == 0) wait_flag(flags + CTL_PROBE / 8 + (grp * 8 + (lane & 3)) * 4, 0);
                    else if (t > 1) wait_flags(flags + 2 * t, t > VSEP ? 0 : ~0u, (t & 15) == 13 ? sb + SM_OFF + (t >> 4) * 16 + 16 : 0, sb + SM_REDO + (t - 1 >> 4));
                    TP(6, t);
                    const int prog = t + (int)(0x94000000u >> (t & 15) * 2 & 3);
                    if (lane == 0) asm volatile("red.release.cta.shared.max.s32 [%0], %1;" ::"r"(sb + SM_PROG), "r"(prog) : "memory");
                }
                mbar_wait_sleep(sb + B_KEMPTY + 8 * kslot, kphase);
                bulk_load_mc<1>(sb + SM_K + kslot * SUB + crank * 8192, ring + (ring_off(grp, t, crank) + c * SUB), sb + B_KFULL + 8 * kslot);
                if (++kslot == KSLOTS) { kslot = 0; kphase ^= 1; }
            };
            auto load_v = [&](int t) {
                if (t >= TOTAL) return;
                if (t < 8) { TP(5, 64 + t); }
                if (t == 0) wait_flag(flags + CTL_PROBE / 8 + (grp * 8 + 4 + (lane & 3)) * 4, sb + SM_REDO);
                else if (((t + 1) & (TOTAL - 1)) <= VSEP) wait_flag(flags + 2 * t + 3, sb + SM_REDO + (t >> 4));
                if (t < 8) { TP(6, 64 + t); }
                const int s = t & 1;
                mbar_wait_sleep(sb + B_VEMPTY + 8 * s, ((t >> 1) & 1) ^ 1);
                bulk_load_mc<3>(sb + SM_V + s * TILE + crank * 8192, ring + ring_off(grp, t, 2 + crank), sb + B_VFULL + 8 * s);
            };
            load_k(0, 0); load_k(0, 1); load_k(0, 2);
            if (lane == 0) q_first(&qmap, sb + SM_Q + 24576, bid * 128 + 64, sb + B_QFULL + 8);
            __syncwarp();
            load_k(1, 0); load_k(1, 1); load_v(0);
#pragma unroll 1
            for (int i = -1; i < TOTAL - 2; i++) {
                if ((i & 15) == 7 && i < TOTAL - 16) pf_scales((i >> 4) + 1, bid);
                if ((i & 15) >= QPF && (i & 15) < QPF + 4 && i < TOTAL - 16)
                    l2_prefetch(P.q + (size_t)(((i >> 4) + 1) * NCTA + bid) * 128 * DH + ((i & 15) - QPF) * 32 * DH, 12288);
                load_k(i + 2, 2); load_k(i + 3, 0); load_k(i + 3, 1);
                load_v(i + 2);
            }
            unsigned int old = 0;
            if (lane == 0) asm volatile("atom.acq_rel.gpu.global.add.u32 %0, [%1], 1;" : "=r"(old) : "l"(state + 8) : "memory");
            if (__shfl_sync(0xffffffffu, old, 0) == NCTA - 1) {
                __syncwarp();
#pragma unroll 1
                for (int g = 0; g < NGROUP; g++) {
                    uint4* c = (uint4*)(P.pages + ctl_off(g));
                    c[1 + lane] = c[33 + lane] = c[CTL_PROBE / 16 + g * 16 + (lane & 15)] = make_uint4(0, 0, 0, 0);
                }
                if (lane < 3) ((uint4*)state)[lane] = make_uint4(0, 0, 0, 0);
            }
        } else {
            const int u = rk & 7;
            const bool isV = rk >= 8;
            const int tfirst = isV ? 1 : 2;
            const int* base = isV ? P.qv : P.qk;
            auto unit_ptr = [&](int t) { return base + ((size_t)((t >> 4) * NGROUP + grp) * SEQ + (t & 15) * 128 + u * 16) * DH; };
            if (warp == 1) {
#pragma unroll 1
                for (int i = 0; i < PFD; i++) {
                    wait_until(clk0, (isV ? PF_TV : PF_TK) + i * PF_DT);
                    l2_prefetch(unit_ptr(tfirst + i), 12288);
                }
#pragma unroll 1
                for (int t = tfirst; t < TOTAL; t++) {
                    mbar_wait_sleep(sb + B_UNIT + 8 * (t & 7), ((t - tfirst) >> 3) & 1);
                    if (t + PFD < TOTAL) l2_prefetch(unit_ptr(t + PFD), 12288);
                    if (lane == 0) {
                        TP(3, t);
                        publish(flags + 2 * t + (isV ? 3 : 0), u, 1 | lds_u32(sb + SM_QBIG) | (lds_u32(sb + SM_VBAD) >> (t >> 4) * 8 & 4));
                        TP(4, t);
                    }
                    __syncwarp();
                    if ((t & 15) == 11 && t < TOTAL - 16) put_v_offset(sb + SM_OFF + (t >> 4) * 16 + 16, v_offset(P, ((t >> 4) + 1) * NGROUP + grp, lane));
                }
            } else {
                const uint64_t pol = policy_evict_first();
                const int pw = warp < 4 ? warp - 2 : warp - 10, c = pw >> 1, h = pw & 1;
                const int hw = lane >> 4, l16 = lane & 15;
                const uint32_t soff = h * 3072 + c * 256 + hw * 768 + l16 * 16;
                const uint32_t doff = (u & 3) * 2048 + c * SUB + h * 512 + hw * 128 +
                                      (isV ? ((((l16 >> 3) * 4 + (l16 & 1)) ^ hw ^ (4 * h)) << 4) + ((l16 >> 1) & 3) * 4
                                           : (((l16 >> 1) ^ hw ^ (4 * h)) << 4) + (l16 & 1) * 8);
                put_v_offset(sb + SM_OFF, v_offset(P, grp, lane));
                wait_until(clk0, isV ? DQ_TV : DQ_TK);
#pragma unroll 1
                for (int t = tfirst; t < TOTAL; t++) {
                    uint32_t n = 0;
                    while (true) {
                        int prog;
                        asm volatile("ld.acquire.cta.shared.u32 %0, [%1];" : "=r"(prog) : "r"(sb + SM_PROG) : "memory");
                        if (prog + LEAD >= t + (isV ? 1 : 0)) break;
                        if (++n > SPIN_LIMIT) __trap();
                        __nanosleep(WPOLL);
                    }
                    if (lane == 0 && pw == 0) { TP(2, t); }
                    const int head = (t >> 4) * NGROUP + grp;
                    const uint8_t* src = (const uint8_t*)unit_ptr(t) + soff;
                    uint8_t* slot = ring + ring_off(grp, t, rk >> 2);
                    if (isV) {
                        const size_t key0 = (size_t)head * SEQ + (t & 15) * 128 + u * 16;
                        const uint32_t voff = sb + SM_OFF + (t >> 4) * 16 + 8;
                        if (c != 0) part_v<false>(P, src, key0, h, slot, doff, pol, voff);
                        else if (!part_v<true>(P, src, key0, h, slot, doff, pol, voff)) { set_flag(sb + SM_QBIG); set_vbad(sb + SM_VBAD + (t >> 4)); }
                    } else {
                        const size_t so = ((size_t)head * 32 + (t & 15) * 2 + (u >> 2)) * DH + c * 64;
                        part_k(P, src, (const uint8_t*)(P.ks + so) + (uint32_t)((lane & 15) * 8), (const uint8_t*)(P.kz + so) + (uint32_t)((lane & 15) * 8),
                               slot, doff, pol, sb + SM_OFF + (t >> 4) * 16);
                    }
                    __syncwarp();
                    if (lane == 0) mbar_arrive(sb + B_UNIT + 8 * (t & 7));
                    const int b = ((t & 15) - (isV ? 9 : 10)) * 6 + pw;
                    if (b >= 0 && b < 16) {
                        mbar_wait(sb + B_QFULL + (b & 8), (t >> 4) & 1);
                        if (q8_big(sb + SM_Q + b * 3072)) {
                            set_flag(sb + SM_QBIG);
                            if (lds_u32(sb + SM_OFF + (t >> 4) * 16)) set_flag(sb + SM_REDO + (t >> 4));
                        }
                        __syncwarp();
                    }
                }
            }
        }
        __syncwarp();
        cluster_arrive();
        cluster_wait();
    } else {
        const int cw = wg - 1, t128 = tid & 127, lane = tid & 31;
        cluster_arrive();
        {
            const int grp = blockIdx.x >> 4, rk = blockIdx.x & 15;
            uint8_t* ring = P.pages + (grp >> 1) * PAGE - (rk & 4) * 2048;
            const uint64_t pol = policy_evict_first();
            const int key0 = cw * 128 + (rk & 7) * 16;
            if (t128 == 0) { TS(cw, 71); }
            bool good = true;
            if (rk >= 8) good = start_v<true>(P, grp, (rk & 7) * 16, ring + ring_off(grp, 0, rk >> 2), (tid >> 5) - 4, lane, pol);
            else start_k(P, grp, key0, ring + ring_off(grp, cw, rk >> 2), t128 >> 5, lane, pol, KOFF);
            if (t128 == 0) { TS(cw, 73); }
            cluster_wait();
            if (!good) set_vbad(sb + SM_VBAD);
            bar_sync(3);
            if (t128 == 0) { TS(cw, 74); }
            if (tid == 128) {
                proxy_fence_global();
                asm volatile("fence.release.gpu;" ::: "memory");
                mbar_wait(sb + B_ROLE, 0);
                asm volatile("st.relaxed.gpu.global.u32 [%0], %1;"
                             ::"l"(P.pages + ctl_off(grp) + CTL_PROBE + (blockIdx.x >> 1) * 32 + (rk & 1) * 4), "r"((uint32_t)TILE_READY | (lds_u32(sb + SM_VBAD) & 4)) : "memory");
                q_first(&qmap, sb + SM_Q, lds_u32(sb + SM_ROLE) * 128, sb + B_QFULL);
                asm volatile("red.release.cta.shared.max.s32 [%0], %1;" ::"r"(sb + SM_PROG), "r"(0) : "memory");
            }
            if (t128 == 0) { TS(cw, 75); }
            __syncwarp();
        }
        asm volatile("setmaxnreg.inc.sync.aligned.u32 224;");
        const int bid = role();
        float o[96], s[64];
        uint32_t p[32];
        Softmax sm;
        sm.fast = true; sm.m0 = 0.f; sm.m1 = 0.f; sm.a0 = 0.f; sm.a1 = 0.f;
        uint32_t kslot = 0, kphase = 0;
        const uint32_t sl = sb & 0x3FFFF;
        const uint32_t qdesc = ((sl + SM_Q + cw * 24576) >> 4) | (1u << 16);
        const uint32_t kdesc0 = ((sl + SM_K) >> 4) | (1u << 16), vdesc0 = ((sl + SM_V) >> 4) | ((SUB >> 4) << 16);
        uint32_t rbar;
        asm volatile("{\n.reg .pred p;\nmapa.shared::cluster.u32 %0, %1, %2;\nsetp.ne.u32 p, %3, 0;\n@p mov.u32 %0, 0;\n}\n"
                     : "=r"(rbar) : "r"(sb + SM_BAR), "r"((t128 >> 5) % CLUSTER), "r"(t128 & ~(32 * (CLUSTER - 1))));
        auto release = [&](uint32_t off) {
            asm volatile("{\n.reg .pred p;\n.reg .u32 a;\nsetp.ne.u32 p, %0, 0;\nadd.u32 a, %0, %1;\n"
                         "@p mbarrier.arrive.shared::cluster.b64 _, [a];\n}\n" ::"r"(rbar), "r"(off) : "memory");
        };
        constexpr uint32_t OKE = B_KEMPTY - SM_BAR, OVE = B_VEMPTY - SM_BAR;
        const int w8 = __shfl_sync(0xffffffffu, (tid >> 5) - 4, 0);
        auto next_q = [&](int item) {
            asm volatile("{\n.reg .pred p;\nelect.sync _|p, 0xffffffff;\n"
                         "@p mbarrier.arrive.expect_tx.shared::cta.b64 _, [%2], 6144;\n"
                         "@p cp.async.bulk.tensor.4d.shared::cluster.global.mbarrier::complete_tx::bytes [%0], [%1, {%3, %3, %3, %4}], [%2];\n}\n"
                         ::"r"(sb + SM_Q + w8 * 6144), "l"(&qmap), "r"(sb + B_QFULL + 8 * cw), "r"(0), "r"((item * NCTA + bid) * 16 + w8 * 2) : "memory");
        };
        auto k_next = [&]() { if (++kslot == KSLOTS) { kslot = 0; kphase ^= 1; } };
        auto k_wait = [&]() { mbar_wait(sb + B_KFULL + 8 * kslot, kphase); };
        auto qk_chunk = [&](int c) {
            const uint32_t kd = kdesc0 + kslot * (SUB >> 4);
#pragma unroll
            for (int k = 0; k < 4; k++) wgmma_ss_n128(s, qdesc + c * 64 + k * 2, kd + k * 2, (c | k) != 0);
            wg_commit();
        };
        auto pv_half = [&](uint32_t vd, int h, int acc) {
#pragma unroll
            for (int k = 4 * h; k < 4 * h + 4; k++)
                wgmma_rs_n192_tb(o, p[4 * k], p[4 * k + 1], p[4 * k + 2], p[4 * k + 3], vd + k * 128, k == 0 ? acc : 1);
            wg_commit();
        };
        auto out_ptr = [&](int item) {
            const uint32_t tl = threadIdx.x & 127;
            __nv_bfloat16* d = P.out + (size_t)((item * NCTA + bid) * 128 + cw * 64) * DH +
                               (uint32_t)(((tl >> 5) * 16 + ((tl & 31) >> 2)) * DH + (tl & 3) * 8);
            asm volatile("" : "+l"(d));
            return d;
        };
        auto out_word = [&](int k, float i0, float i1, float c) {
            const int b = 16 * (k >> 1) + 2 * (k & 1);
            const float i = (k & 1) ? i1 : i0;
            return make_uint4(pack_bf16(fmaf(o[b], i, c), fmaf(o[b + 1], i, c)), pack_bf16(fmaf(o[b + 8], i, c), fmaf(o[b + 9], i, c)),
                              pack_bf16(fmaf(o[b + 4], i, c), fmaf(o[b + 5], i, c)), pack_bf16(fmaf(o[b + 12], i, c), fmaf(o[b + 13], i, c)));
        };
        auto v_back = [&](int item) { return __uint_as_float(lds_u32(sb + SM_OFF + item * 16 + 12)); };
        auto put_word = [&](__nv_bfloat16* d, int k, uint4 w) { __stcs((uint4*)(d + (k & 1) * 8 * DH + (k >> 1) * 32), w); };
        auto store_o = [&](__nv_bfloat16* d, float i0, float i1, float c, int n) {
#pragma unroll
            for (int k = 0; k < n; k++) put_word(d, k, out_word(k, i0, i1, c));
        };

#pragma unroll
        for (int i = 0; i < 96; i++) asm volatile("" : "=f"(o[i]));
        if (cw == 0) bar_arrive(1);

        if (t128 == 0) { TS(cw, 77); }
        mbar_wait(sb + B_QFULL + 8 * cw, 0);
        if (t128 == 0) { TS(cw, 78); }
        k_wait();
        if (t128 == 0) { TS(cw, 79); }
        bar_sync(1 + cw);
        wg_fence();
        qk_chunk(0); k_next(); k_wait(); qk_chunk(1); k_next(); k_wait(); qk_chunk(2); k_next();
        bar_arrive(1 + (cw ^ 1));
        wg_wait<2>(); release(OKE); wg_wait<1>(); release(OKE + 8); wg_wait<0>(); release(OKE + 16);
        fence_regs(s);
        sm.run<true>(s);
        sm.pack(s, p);

        constexpr int NOW = 9;
        float i0, i1, vb;
        __nv_bfloat16* d;
        auto step = [&](int t, auto LAST, auto FIRST) {
            constexpr bool last = decltype(LAST)::value;
            constexpr bool first = decltype(FIRST)::value;
            const uint32_t vd = vdesc0 + (t & 1) * (TILE >> 4);
            uint4 w[12 - NOW];
            if (last) {
                d = out_ptr(t >> 4);
                sm.finish(i0, i1, sb + SM_REDO + (t >> 4));
                vb = v_back(t >> 4);
                mbar_wait(sb + B_QFULL + 8 * cw, ((t + 1) >> 4) & 1);
            }
            k_wait();
            bar_sync(1 + cw);
            TF(0);
            fence_regs(p);
            wg_fence();
            const uint32_t e0 = kslot; qk_chunk(0); k_next(); k_wait();
            const uint32_t e1 = kslot; qk_chunk(1); k_next(); k_wait();
            const uint32_t e2 = kslot; qk_chunk(2); k_next();
            TF(1);
            if (first) {
                fence_regs(o);
#pragma unroll
                for (int k = 0; k < 12 - NOW; k++) {
                    w[k] = out_word(NOW + k, i0, i1, vb);
                    asm volatile("" : "+r"(w[k].x), "+r"(w[k].y), "+r"(w[k].z), "+r"(w[k].w));
                }
            } else sm.rescale(o);
            fence_regs(o);
            wg_wait<2>(); release(OKE + 8 * e0);
            TF(2);
            mbar_wait(sb + B_VFULL + 8 * (t & 1), (t >> 1) & 1);
            wg_fence();
            pv_half(vd, 0, !first && (last || t != 0));
            wg_wait<2>(); release(OKE + 8 * e1);
            pv_half(vd, 1, 1);
            bar_arrive(1 + (cw ^ 1));
            TF(3);
            wg_wait<2>(); release(OKE + 8 * e2);
            TF(4);
            if (!last && !first && (t & 15) == 14 && t < TOTAL - 2) next_q((t >> 4) + 1);
            fence_regs(s);
            sm.run<last>(s);
            fence_regs(s);
            TF(5);
            wg_wait<0>();
            release(OVE + 8 * (t & 1));
            if (first) {
#pragma unroll
                for (int k = 0; k < 12 - NOW; k++) put_word(d, NOW + k, w[k]);
            }
            fence_regs(o);
            if (last) store_o(d, i0, i1, vb, NOW);
            TF(6);
            sm.pack(s, p);
            fence_regs(p);
            TF(7);
        };
#pragma unroll 1
        for (int t = 0;;) {
#pragma unroll 1
            do { step(t, Flag<false>(), Flag<false>()); t++; } while ((t & 15) != 15);
            if (t == TOTAL - 1) break;
            step(t, Flag<true>(), Flag<false>());
            step(t + 1, Flag<false>(), Flag<true>());
            t += 2;
        }
        {
            constexpr int t = TOTAL - 1;
            const uint32_t vd = vdesc0 + (t & 1) * (TILE >> 4);
            d = out_ptr(3);
            TS(cw, 72);
            sm.rescale(o);
            sm.finish(i0, i1, sb + SM_REDO + 3);
            vb = v_back(3);
            mbar_wait(sb + B_VFULL + 8 * (t & 1), (t >> 1) & 1);
            bar_sync(1 + cw);
            fence_regs(o); fence_regs(p);
            wg_fence();
            pv_half(vd, 0, 1); pv_half(vd, 1, 1);
            bar_arrive(2 + cw);
            wg_wait<0>();
            TS(cw, 76);
            cluster_arrive();
            fence_regs(o);
            uint32_t x[12];
#pragma unroll
            for (int k = 0; k < 12; k++) {
                const uint4 w = out_word(k, i0, i1, k < 2 ? vb : __uint_as_float(__float_as_uint(vb) ^ (x[k - 2] & P.zero)));
                put_word(d, k, w);
                x[k] = w.w;
            }
        }
        if (cw == 0) bar_sync(3);
        uint32_t redo = lds_u32(sb + SM_REDO), qphase = 0;
        if (redo) bar_sync(4);
#pragma unroll 1
        for (int item = 0; redo; item++, redo >>= 8) {
            if (!(redo & 255)) continue;
            uint8_t* img = smem_raw + (sb - smem_u32(smem_raw));
            const uint64_t pol = policy_evict_first();
            const int head = item * NGROUP + (bid >> 4);
            next_q(item);
            sm.fast = false; sm.m0 = -INFINITY; sm.m1 = -INFINITY; sm.l0 = 0.f; sm.l1 = 0.f;
#pragma unroll 1
            for (int t = 0; t < 16; t++) {
#pragma unroll 2
                for (int a = 0; a < 4; a++) start_k(P, head, t * 128 + (2 * a + cw) * 16, img + SM_K, w8 & 3, lane, pol, 0.f);
#pragma unroll 4
                for (int a = 0; a < 8; a++) start_v<false>(P, head, t * 128 + a * 16, img + SM_V, w8, lane, pol);
                asm volatile("fence.proxy.async.shared::cta;" ::: "memory");
                bar_sync(3);
                mbar_wait(sb + B_QFULL + 8 * cw, qphase);
                wg_fence();
                kslot = 0; qk_chunk(0); kslot = 1; qk_chunk(1); kslot = 2; qk_chunk(2);
                wg_wait<0>();
                fence_regs(s);
                sm.run<false>(s);
                sm.pack(s, p);
                sm.rescale(o);
                fence_regs(o); fence_regs(p);
                wg_fence();
                pv_half(vdesc0, 0, t != 0); pv_half(vdesc0, 1, 1);
                wg_wait<0>();
                fence_regs(o);
                bar_sync(3);
            }
            sm.finish(i0, i1, sb + SM_REDO + 4);
            store_o(out_ptr(item), i0, i1, 0.f, 12);
            qphase ^= 1;
        }
        cluster_wait();
    }
}

typedef CUresult (*EncodeFn)(CUtensorMap*, CUtensorMapDataType, cuuint32_t, void*, const cuuint64_t*, const cuuint64_t*,
                             const cuuint32_t*, const cuuint32_t*, CUtensorMapInterleave, CUtensorMapSwizzle,
                             CUtensorMapL2promotion, CUtensorMapFloatOOBfill);

}

extern "C" void kernel_launch(void* const* d_in, const int* in_sizes, int n_in, void* d_out, int out_size) {
    cudaLaunchConfig_t cfg = {};
    cudaLaunchAttribute at[1];
    at[0].id = cudaLaunchAttributeClusterDimension;
    at[0].val.clusterDim.x = CLUSTER; at[0].val.clusterDim.y = 1; at[0].val.clusterDim.z = 1;
    cfg.attrs = at; cfg.numAttrs = 1;
    cfg.blockDim = dim3(512); cfg.dynamicSmemBytes = SMEM_BYTES; cfg.stream = cudaStreamPerThread;

    static EncodeFn encode = nullptr;
    static uintptr_t scratch;
    if (!encode) {
        void* fn = nullptr;
        cudaDriverEntryPointQueryResult st;
        cudaGetDriverEntryPoint("cuTensorMapEncodeTiled", &fn, cudaEnableDefault, &st);
        encode = (EncodeFn)fn;
        cudaFuncSetAttribute(kvq_attn_kernel, cudaFuncAttributeMaxDynamicSharedMemorySize, SMEM_BYTES);
        cudaGetSymbolAddress((void**)&scratch, g_scratch);
    }
    CUtensorMap qmap;
    const cuuint64_t gdim[4] = {64, 8, 3, (cuuint64_t)NH * SEQ / 8};
    const cuuint64_t gstride[3] = {DH * 2, 128, 8 * DH * 2};
    const cuuint32_t box[4] = {64, 8, 3, 2};
    const cuuint32_t estr[4] = {1, 1, 1, 1};
    encode(&qmap, CU_TENSOR_MAP_DATA_TYPE_BFLOAT16, 4, d_in[0], gdim, gstride, box, estr, CU_TENSOR_MAP_INTERLEAVE_NONE,
           CU_TENSOR_MAP_SWIZZLE_128B, CU_TENSOR_MAP_L2_PROMOTION_L2_128B, CU_TENSOR_MAP_FLOAT_OOB_FILL_NONE);
    Params P;
    P.q = (const __nv_bfloat16*)d_in[0];
    P.qk = (const int*)d_in[1]; P.qv = (const int*)d_in[2];
    P.ks = (const __nv_bfloat16*)d_in[3]; P.kz = (const __nv_bfloat16*)d_in[4];
    P.vs = (const __nv_bfloat16*)d_in[5]; P.vz = (const __nv_bfloat16*)d_in[6];
    P.out = (__nv_bfloat16*)d_out;
    P.pages = (uint8_t*)((scratch + PAGE - 1) & ~(uintptr_t)(PAGE - 1));
    P.zero = 0;
    cfg.gridDim = dim3(NCTA);
    cudaLaunchKernelEx(&cfg, kvq_attn_kernel, P, qmap);
}
```

```cpp
#include <cuda_runtime.h>
#include <cuda_bf16.h>
#include <cuda.h>
#include <stdint.h>

#define LEAD 2
#define Q_T0 1400
#define Q_DT 250
#define POLL_T 4100
#define PF_TK 4500
#define PF_TV 5100
#define PF_DT 1100
#define PFD 1
#define DQ_TK 5600
#define DQ_TV 5800
#define WPOLL 350
#define KOFF 1.25f
#define QPF 5
#define VEXP (-10)
#define VOFF 1.25f
#define TF0 29
#define SPIN_LIMIT (1u << 22)

namespace {

constexpr int CLUSTER = 2;
constexpr int NH = 32, SEQ = 2048, DH = 192;
constexpr int NGROUP = 8, GSIZE = 16, TOTAL = 64;
constexpr int NCTA = NGROUP * GSIZE;
constexpr uint32_t TILE = 128 * DH * 2;
constexpr uint32_t SUB = 16384;
constexpr int KSLOTS = 5;
constexpr int RING = 8;
static_assert(RING >= 2 * LEAD + 4, "a ring slot may only be rewritten after every CTA of the group has loaded it");

constexpr uint32_t SM_Q = 0;
constexpr uint32_t SM_K = 49152;
constexpr uint32_t SM_V = SM_K + KSLOTS * SUB;
constexpr uint32_t SM_BAR = SM_V + 2 * TILE;
constexpr uint32_t B_KFULL = SM_BAR, B_KEMPTY = B_KFULL + 8 * KSLOTS;
constexpr uint32_t B_VFULL = B_KEMPTY + 8 * KSLOTS, B_VEMPTY = B_VFULL + 16;
constexpr uint32_t B_QFULL = B_VEMPTY + 16;
constexpr uint32_t B_UNIT = B_QFULL + 16;
constexpr uint32_t B_ROLE = B_UNIT + 64, SM_ROLE = B_ROLE + 8;
constexpr uint32_t SM_LAT = B_ROLE + 16;
constexpr uint32_t SM_OFF = SM_LAT + 32;
constexpr uint32_t SM_PROG = SM_OFF + 80;
constexpr uint32_t SM_QBIG = SM_PROG + 4;
constexpr uint32_t SM_REDO = SM_PROG + 8;
constexpr uint32_t SM_VBAD = SM_PROG + 12;
constexpr uint32_t SMEM_BYTES = SM_PROG + 16 + 1024;

constexpr uint32_t PAGE = 2u << 20, CTL_STATE = 1536, CTL_PROBE = 2048;
__device__ __align__(1024) uint8_t g_scratch[(NGROUP / 2 + 1) * PAGE];
__device__ __forceinline__ uint32_t ring_off(int g, int t, int j) {
    const uint32_t s = t % RING, x = (j ^ (j >> 1) ^ (s >> 1) ^ g) & 1;
    return ((s * 4 + j) << 16) + (x ? 4096 : 12288);
}
__device__ __forceinline__ uint32_t ctl_off(int g) { return (g >> 1) * PAGE + ((g & 1) ? 53248 : 0); }

#define TR(ch, idx)
#define TP(ch, idx)
#define TRC(ch, idx)
#define TS(ch, idx)
#define TF(i)

constexpr uint32_t ST_OPEN = 0x80000000u, PAR_OPEN = 32;
constexpr unsigned long long TILE_READY = 0x0101010101010101ull;
constexpr uint32_t FLAG_VBAD = 0x04040404u;

__device__ __forceinline__ uint32_t smem_u32(const void* p) { return (uint32_t)__cvta_generic_to_shared(p); }
__device__ __forceinline__ void mbar_init(uint32_t bar, uint32_t cnt) {
    asm volatile("mbarrier.init.shared::cta.b64 [%0], %1;" ::"r"(bar), "r"(cnt) : "memory");
}
__device__ __forceinline__ void mbar_arrive(uint32_t bar) {
    asm volatile("mbarrier.arrive.shared::cta.b64 _, [%0];" ::"r"(bar) : "memory");
}
__device__ __forceinline__ void mbar_expect_tx(uint32_t bar, uint32_t bytes) {
    asm volatile("mbarrier.arrive.expect_tx.shared::cta.b64 _, [%0], %1;" ::"r"(bar), "r"(bytes) : "memory");
}
__device__ __forceinline__ void mbar_wait(uint32_t bar, uint32_t parity) {
    asm volatile("{\n.reg .pred p;\n.reg .u32 n;\n"
                 "mbarrier.try_wait.parity.shared::cta.b64 p, [%0], %1;\n@p bra DONE;\nmov.u32 n, 0;\n"
                 "LOOP:\nmbarrier.try_wait.parity.shared::cta.b64 p, [%0], %1;\n@p bra DONE;\n"
                 "add.u32 n, n, 1;\nsetp.lt.u32 p, n, %2;\n@p bra LOOP;\ntrap;\nDONE:\n}\n"
                 ::"r"(bar), "r"(parity), "n"(SPIN_LIMIT) : "memory");
}
__device__ __forceinline__ void mbar_wait_sleep(uint32_t bar, uint32_t parity) {
    asm volatile("{\n.reg .pred p;\n.reg .u32 n;\nmov.u32 n, 0;\n"
                 "LOOP:\nmbarrier.try_wait.parity.shared::cta.b64 p, [%0], %1, %3;\n@p bra DONE;\n"
                 "add.u32 n, n, 1;\nsetp.lt.u32 p, n, %2;\n@p bra LOOP;\ntrap;\nDONE:\n}\n"
                 ::"r"(bar), "r"(parity), "n"(1 << 18), "r"(10000) : "memory");
}
template <int N> __device__ __forceinline__ void bulk_load_mc(uint32_t dst, const void* src, uint32_t bar) {
    asm volatile("{\n.reg .pred p, q;\nelect.sync _|p, 0xffffffff;\nsetp.eq.and.u32 q, %5, 3, p;\n"
                 "@p mbarrier.arrive.expect_tx.shared::cta.b64 _, [%2], %4;\n"
                 "@p cp.async.bulk.shared::cluster.global.mbarrier::complete_tx::bytes.multicast::cluster [%0], [%1], 8192, [%2], %3;\n"
                 "@q cp.async.bulk.shared::cluster.global.mbarrier::complete_tx::bytes.multicast::cluster [%0 + 16384], [%1 + 16384], 8192, [%2], %3;\n"
                 "@q cp.async.bulk.shared::cluster.global.mbarrier::complete_tx::bytes.multicast::cluster [%0 + 32768], [%1 + 32768], 8192, [%2], %3;\n}\n"
                 ::"r"(dst), "l"(src), "r"(bar), "h"((uint16_t)((1 << CLUSTER) - 1)), "n"(N * SUB), "n"(N) : "memory");
}
__device__ __forceinline__ void tma_load_q16(uint32_t dst, const CUtensorMap* map, int g, uint32_t bar) {
    asm volatile("cp.async.bulk.tensor.4d.shared::cluster.global.mbarrier::complete_tx::bytes [%0], [%1, {%3, %3, %3, %4}], [%2];"
                 ::"r"(dst), "l"(map), "r"(bar), "r"(0), "r"(g) : "memory");
}
__device__ __forceinline__ void l2_prefetch(const void* p, uint32_t bytes) {
    asm volatile("{\n.reg .pred p;\nelect.sync _|p, 0xffffffff;\n@p cp.async.bulk.prefetch.L2.global [%0], %1;\n}\n" ::"l"(p), "r"(bytes) : "memory");
}
__device__ __forceinline__ uint64_t policy_evict_first() {
    uint64_t pol;
    asm volatile("createpolicy.fractional.L2::evict_first.b64 %0, 1.0;" : "=l"(pol));
    return pol;
}
__device__ __forceinline__ void wg_fence() { asm volatile("wgmma.fence.sync.aligned;" ::: "memory"); }
__device__ __forceinline__ void wg_commit() { asm volatile("wgmma.commit_group.sync.aligned;" ::: "memory"); }
template <int N> __device__ __forceinline__ void wg_wait() { asm volatile("wgmma.wait_group.sync.aligned %0;" ::"n"(N) : "memory"); }
__device__ __forceinline__ void bar_sync(int id) { asm volatile("bar.sync %0, 256;" ::"r"(id) : "memory"); }
__device__ __forceinline__ void bar_arrive(int id) { asm volatile("bar.arrive %0, 256;" ::"r"(id) : "memory"); }
__device__ __forceinline__ float ex2(float x) { float y; asm("ex2.approx.ftz.f32 %0, %1;" : "=f"(y) : "f"(x)); return y; }
__device__ __forceinline__ float rcp(float x) { float y; asm volatile("rcp.approx.ftz.f32 %0, %1;" : "=f"(y) : "f"(x)); return y; }
__device__ __forceinline__ uint32_t pack_bf16(float lo, float hi) {
    uint32_t r; asm("cvt.rn.bf16x2.f32 %0, %1, %2;" : "=r"(r) : "f"(hi), "f"(lo)); return r;
}
__device__ __forceinline__ uint32_t bf2_add(uint32_t a, uint32_t b) { uint32_t r; asm("add.rn.bf16x2 %0, %1, %2;" : "=r"(r) : "r"(a), "r"(b)); return r; }
__device__ __forceinline__ uint32_t bf2_sub(uint32_t a, uint32_t b) { uint32_t r; asm("sub.rn.bf16x2 %0, %1, %2;" : "=r"(r) : "r"(a), "r"(b)); return r; }
__device__ __forceinline__ uint32_t bf2_mul(uint32_t a, uint32_t b) { uint32_t r; asm("mul.rn.bf16x2 %0, %1, %2;" : "=r"(r) : "r"(a), "r"(b)); return r; }
__device__ __forceinline__ uint32_t bf2_fma(uint32_t a, uint32_t b, uint32_t c) { uint32_t r; asm("fma.rn.bf16x2 %0, %1, %2, %3;" : "=r"(r) : "r"(a), "r"(b), "r"(c)); return r; }
__device__ __forceinline__ float bf_lo(uint32_t w) { return __uint_as_float(w << 16); }
__device__ __forceinline__ float bf_hi(uint32_t w) { return __uint_as_float(w & 0xffff0000u); }
__device__ __forceinline__ int4 ldg_stream(const void* p, uint64_t pol) {
    int4 v;
    asm volatile("ld.global.nc.L1::no_allocate.L2::cache_hint.v4.s32 {%0,%1,%2,%3}, [%4], %5;"
                 : "=r"(v.x), "=r"(v.y), "=r"(v.z), "=r"(v.w) : "l"(p), "l"(pol));
    return v;
}
__device__ __forceinline__ uint4 lds_v4(uint32_t a) {
    uint4 v;
    asm volatile("ld.shared.v4.u32 {%0,%1,%2,%3}, [%4];" : "=r"(v.x), "=r"(v.y), "=r"(v.z), "=r"(v.w) : "r"(a) : "memory");
    return v;
}
__device__ __forceinline__ uint32_t lds_u32(uint32_t a) { uint32_t v; asm volatile("ld.shared.u32 %0, [%1];" : "=r"(v) : "r"(a) : "memory"); return v; }
template <int R> __device__ __forceinline__ void fence_regs(float (&d)[R]) {
#pragma unroll
    for (int i = 0; i < R; i++) asm volatile("" : "+f"(d[i])::"memory");
}
template <int R> __device__ __forceinline__ void fence_regs(uint32_t (&d)[R]) {
#pragma unroll
    for (int i = 0; i < R; i++) asm volatile("" : "+r"(d[i])::"memory");
}
template <bool B> struct Flag { static constexpr bool value = B; };

__device__ __forceinline__ void wgmma_ss_n128(float (&d)[64], uint32_t alo, uint32_t blo, int scale_d) {
    asm volatile(
        "{\n.reg .pred p;\n.reg .b64 da, db;\nsetp.ne.b32 p, %66, 0;\nmov.b64 da, {%64, 0x400000C0};\nmov.b64 db, {%65, 0x40000040};\n"
        "wgmma.mma_async.sync.aligned.m64n128k16.f32.bf16.bf16 "
        "{%0, %1, %2, %3, %4, %5, %6, %7, %8, %9, %10, %11, %12, %13, %14, %15, "
        "%16, %17, %18, %19, %20, %21, %22, %23, %24, %25, %26, %27, %28, %29, %30, %31, "
        "%32, %33, %34, %35, %36, %37, %38, %39, %40, %41, %42, %43, %44, %45, %46, %47, "
        "%48, %49, %50, %51, %52, %53, %54, %55, %56, %57, %58, %59, %60, %61, %62, %63}, "
        "da, db, p, 1, 1, 0, 0;\n}\n"
        :
          "+f"(d[0]), "+f"(d[1]), "+f"(d[2]), "+f"(d[3]), "+f"(d[4]), "+f"(d[5]), "+f"(d[6]), "+f"(d[7]),
          "+f"(d[8]), "+f"(d[9]), "+f"(d[10]), "+f"(d[11]), "+f"(d[12]), "+f"(d[13]), "+f"(d[14]), "+f"(d[15]),
          "+f"(d[16]), "+f"(d[17]), "+f"(d[18]), "+f"(d[19]), "+f"(d[20]), "+f"(d[21]), "+f"(d[22]), "+f"(d[23]),
          "+f"(d[24]), "+f"(d[25]), "+f"(d[26]), "+f"(d[27]), "+f"(d[28]), "+f"(d[29]), "+f"(d[30]), "+f"(d[31]),
          "+f"(d[32]), "+f"(d[33]), "+f"(d[34]), "+f"(d[35]), "+f"(d[36]), "+f"(d[37]), "+f"(d[38]), "+f"(d[39]),
          "+f"(d[40]), "+f"(d[41]), "+f"(d[42]), "+f"(d[43]), "+f"(d[44]), "+f"(d[45]), "+f"(d[46]), "+f"(d[47]),
          "+f"(d[48]), "+f"(d[49]), "+f"(d[50]), "+f"(d[51]), "+f"(d[52]), "+f"(d[53]), "+f"(d[54]), "+f"(d[55]),
          "+f"(d[56]), "+f"(d[57]), "+f"(d[58]), "+f"(d[59]), "+f"(d[60]), "+f"(d[61]), "+f"(d[62]), "+f"(d[63])
        : "r"(alo), "r"(blo), "r"(scale_d));
}

__device__ __forceinline__ void wgmma_rs_n192_tb(float (&d)[96], uint32_t a0, uint32_t a1, uint32_t a2, uint32_t a3, uint32_t blo, int scale_d) {
    asm volatile(
        "{\n.reg .pred p;\n.reg .b64 db;\nsetp.ne.b32 p, %101, 0;\nmov.b64 db, {%100, 0x40000040};\n"
        "wgmma.mma_async.sync.aligned.m64n192k16.f32.bf16.bf16 "
        "{%0, %1, %2, %3, %4, %5, %6, %7, %8, %9, %10, %11, %12, %13, %14, %15, "
        "%16, %17, %18, %19, %20, %21, %22, %23, %24, %25, %26, %27, %28, %29, %30, %31, "
        "%32, %33, %34, %35, %36, %37, %38, %39, %40, %41, %42, %43, %44, %45, %46, %47, "
        "%48, %49, %50, %51, %52, %53, %54, %55, %56, %57, %58, %59, %60, %61, %62, %63, "
        "%64, %65, %66, %67, %68, %69, %70, %71, %72, %73, %74, %75, %76, %77, %78, %79, "
        "%80, %81, %82, %83, %84, %85, %86, %87, %88, %89, %90, %91, %92, %93, %94, %95}, "
        "{%96, %97, %98, %99}, db, p, 1, 1, 1;\n}\n"
        :
          "+f"(d[0]), "+f"(d[1]), "+f"(d[2]), "+f"(d[3]), "+f"(d[4]), "+f"(d[5]), "+f"(d[6]), "+f"(d[7]),
          "+f"(d[8]), "+f"(d[9]), "+f"(d[10]), "+f"(d[11]), "+f"(d[12]), "+f"(d[13]), "+f"(d[14]), "+f"(d[15]),
          "+f"(d[16]), "+f"(d[17]), "+f"(d[18]), "+f"(d[19]), "+f"(d[20]), "+f"(d[21]), "+f"(d[22]), "+f"(d[23]),
          "+f"(d[24]), "+f"(d[25]), "+f"(d[26]), "+f"(d[27]), "+f"(d[28]), "+f"(d[29]), "+f"(d[30]), "+f"(d[31]),
          "+f"(d[32]), "+f"(d[33]), "+f"(d[34]), "+f"(d[35]), "+f"(d[36]), "+f"(d[37]), "+f"(d[38]), "+f"(d[39]),
          "+f"(d[40]), "+f"(d[41]), "+f"(d[42]), "+f"(d[43]), "+f"(d[44]), "+f"(d[45]), "+f"(d[46]), "+f"(d[47]),
          "+f"(d[48]), "+f"(d[49]), "+f"(d[50]), "+f"(d[51]), "+f"(d[52]), "+f"(d[53]), "+f"(d[54]), "+f"(d[55]),
          "+f"(d[56]), "+f"(d[57]), "+f"(d[58]), "+f"(d[59]), "+f"(d[60]), "+f"(d[61]), "+f"(d[62]), "+f"(d[63]),
          "+f"(d[64]), "+f"(d[65]), "+f"(d[66]), "+f"(d[67]), "+f"(d[68]), "+f"(d[69]), "+f"(d[70]), "+f"(d[71]),
          "+f"(d[72]), "+f"(d[73]), "+f"(d[74]), "+f"(d[75]), "+f"(d[76]), "+f"(d[77]), "+f"(d[78]), "+f"(d[79]),
          "+f"(d[80]), "+f"(d[81]), "+f"(d[82]), "+f"(d[83]), "+f"(d[84]), "+f"(d[85]), "+f"(d[86]), "+f"(d[87]),
          "+f"(d[88]), "+f"(d[89]), "+f"(d[90]), "+f"(d[91]), "+f"(d[92]), "+f"(d[93]), "+f"(d[94]), "+f"(d[95])
        : "r"(a0), "r"(a1), "r"(a2), "r"(a3), "r"(blo), "r"(scale_d));
}

struct Params {
    const int* qk; const int* qv;
    const __nv_bfloat16* ks; const __nv_bfloat16* kz; const __nv_bfloat16* vs; const __nv_bfloat16* vz;
    const __nv_bfloat16* q; __nv_bfloat16* out;
    uint8_t* pages;
    uint32_t zero;
};

constexpr float SCALE = 0.07216878364870322f * 1.4426950408889634f;
constexpr uint32_t VSCALE2 = 0x3f80u | ((uint32_t)(127 + VEXP) << 23);
__device__ __forceinline__ void set_flag(uint32_t flag) { asm volatile("st.shared.u8 [%0], %1;" ::"r"(flag), "r"(2) : "memory"); }
constexpr float QNORM2 = 14.f;
__device__ __forceinline__ void sq_acc(uint32_t (&x)[4], uint4 v) {
    x[0] = bf2_fma(v.x, v.x, x[0]); x[1] = bf2_fma(v.y, v.y, x[1]); x[2] = bf2_fma(v.z, v.z, x[2]); x[3] = bf2_fma(v.w, v.w, x[3]);
}
__device__ __forceinline__ float sq_sum(const uint32_t (&x)[4]) {
    const uint32_t y = bf2_add(bf2_add(x[0], x[1]), bf2_add(x[2], x[3]));
    return bf_lo(y) + bf_hi(y);
}
__device__ __forceinline__ bool q8_big(uint32_t rows) {
    uint32_t lane;
    asm volatile("mov.u32 %0, %laneid;" : "=r"(lane));
    uint32_t x[4] = {0, 0, 0, 0}, y[4] = {0, 0, 0, 0};
#pragma unroll
    for (int a = 0; a < 3; a++) { sq_acc(x, lds_v4(rows + lane * 16 + a * 1024)); sq_acc(y, lds_v4(rows + lane * 16 + a * 1024 + 512)); }
    float f = sq_sum(x), g = sq_sum(y);
#pragma unroll
    for (int m = 1; m < 8; m *= 2) { f += __shfl_xor_sync(0xffffffffu, f, m); g += __shfl_xor_sync(0xffffffffu, g, m); }
    return !(f <= QNORM2 && g <= QNORM2);
}

struct KScale {
    float s0, s1, s2, s3, n0, n1, n2, n3;
    __device__ __forceinline__ KScale(uint2 sc, uint2 z, float c) {
        s0 = bf_lo(sc.x) * SCALE; s1 = bf_hi(sc.x) * SCALE; s2 = bf_lo(sc.y) * SCALE; s3 = bf_hi(sc.y) * SCALE;
        n0 = fmaf(-bf_lo(z.x), s0, c); n1 = fmaf(-bf_hi(z.x), s1, c); n2 = fmaf(-bf_lo(z.y), s2, c); n3 = fmaf(-bf_hi(z.y), s3, c);
    }
    __device__ __forceinline__ uint2 operator()(int4 v) const {
        return make_uint2(pack_bf16(fmaf((float)v.x, s0, n0), fmaf((float)v.y, s1, n1)),
                          pack_bf16(fmaf((float)v.z, s2, n2), fmaf((float)v.w, s3, n3)));
    }
};
template <bool CHECK>
__device__ __forceinline__ uint32_t deq_v4(int4 v, uint32_t zs, uint32_t off, uint8_t* d0, uint8_t* d1) {
    const uint32_t z = __byte_perm(zs, 0, 0x1010), sc = __byte_perm(zs, 0, 0x3232);
    const uint32_t a = bf2_sub(pack_bf16((float)v.x, (float)v.y), z), b = bf2_sub(pack_bf16((float)v.z, (float)v.w), z);
    *(uint32_t*)d0 = bf2_fma(a, sc, off);
    *(uint32_t*)d1 = bf2_fma(b, sc, off);
    uint32_t far = 0;
    if (CHECK)
        asm("{\n.reg .b32 x, t;\nmax.xorsign.abs.bf16x2 x, %1, %2;\nmul.rn.bf16x2 x, x, %3;\nabs.bf16x2 x, x;\n"
            "mul.rn.bf16x2 t, %4, %5;\nset.ge.u32.bf16x2 %0, x, t;\n}\n" : "=r"(far) : "r"(a), "r"(b), "r"(sc), "r"(off), "r"(0x3e803e80u));
    return far;
}
__device__ __forceinline__ bool v_token_ok(uint32_t zs, uint32_t off) { return (off == 0) | (fabsf(bf_lo(zs) * bf_hi(zs)) <= 4.f * bf_lo(off)); }
__device__ __forceinline__ uint32_t v_offset(const Params& P, int head, int lane) {
    float w = __bfloat162float(__ldg(P.vs + (size_t)head * SEQ + lane)) * __bfloat162float(__ldg(P.vz + (size_t)head * SEQ + lane));
#pragma unroll
    for (int m = 16; m >= 1; m >>= 1) w += __shfl_xor_sync(0xffffffffu, w, m);
    w = fmaxf(w * (VOFF / 32.f * __uint_as_float((127 + VEXP) << 23)), 0.f);
    const uint32_t u = (__float_as_uint(w) + 0x00080000u) & 0xfff00000u;
    return u | u >> 16;
}
__device__ __forceinline__ void put_v_offset(uint32_t entry, uint32_t off) {
    asm volatile("st.shared.v2.b32 [%0 + 8], {%1, %2};" ::"r"(entry), "r"(off), "r"(__float_as_uint(-bf_lo(off) * __uint_as_float((127 - VEXP) << 23))) : "memory");
}
__device__ __forceinline__ void set_vbad(uint32_t flag) { asm volatile("st.shared.u8 [%0], %1;" ::"r"(flag), "r"(4) : "memory"); }
__device__ __forceinline__ uint32_t load_vzs(const Params& P, size_t idx) {
    return bf2_mul((uint32_t)__bfloat16_as_ushort(__ldg(P.vz + idx)) | ((uint32_t)__bfloat16_as_ushort(__ldg(P.vs + idx)) << 16), VSCALE2);
}
__device__ __forceinline__ void part_k(const Params& P, const uint8_t* src, const uint8_t* sp, const uint8_t* zp, uint8_t* slot, uint32_t doff, uint64_t pol,
                                       uint32_t koff) {
    int4 v[4];
    uint2 sc = __ldg((const uint2*)sp);
    const uint2 z = __ldg((const uint2*)zp);
#pragma unroll
    for (int a = 0; a < 4; a++) v[a] = ldg_stream(src + (a & 1) * 1536 + (a >> 1) * 6144, pol);
    uint32_t lo[4], hi[4];
    const float c = __uint_as_float(lds_u32(koff));
    {
        sc.x ^= v[3].w & P.zero;
        const float s0 = bf_lo(sc.x) * SCALE, s1 = bf_hi(sc.x) * SCALE, n0 = fmaf(-bf_lo(z.x), s0, c), n1 = fmaf(-bf_hi(z.x), s1, c);
#pragma unroll
        for (int a = 0; a < 4; a++) lo[a] = pack_bf16(fmaf((float)v[a].x, s0, n0), fmaf((float)v[a].y, s1, n1));
    }
    {
        sc.y ^= lo[3] & P.zero;
        const float s0 = bf_lo(sc.y) * SCALE, s1 = bf_hi(sc.y) * SCALE, n0 = fmaf(-bf_lo(z.y), s0, c), n1 = fmaf(-bf_hi(z.y), s1, c);
#pragma unroll
        for (int a = 0; a < 4; a++) hi[a] = pack_bf16(fmaf((float)v[a].z, s0, n0), fmaf((float)v[a].w, s1, n1));
    }
    doff ^= lo[3] & P.zero;
#pragma unroll
    for (int a = 0; a < 4; a++) *(uint2*)(slot + ((a & 1) ? (doff ^ 32) + 256 : doff) + (a >> 1) * 1024) = make_uint2(lo[a], hi[a]);
}
template <bool CHECK>
__device__ __forceinline__ bool part_v(const Params& P, const uint8_t* src, size_t key0, int h, uint8_t* slot, uint32_t doff, uint64_t pol, uint32_t voff) {
    int4 v[4];
#pragma unroll
    for (int a = 0; a < 4; a++) v[a] = ldg_stream(src + (a & 1) * 1536 + (a >> 1) * 6144, pol);
    uint32_t ln;
    asm volatile("mov.u32 %0, %laneid;" : "=r"(ln));
    const uint32_t zs = load_vzs(P, key0 + (ln & 15));
    int r0 = 4 * h + (ln >> 4);
    r0 ^= v[3].w & P.zero;
    doff ^= v[3].w & P.zero;
    uint8_t* d0 = slot + doff; uint8_t* d1 = slot + (doff ^ 32);
    const uint32_t off = lds_u32(voff);
    uint32_t m = 0;
#pragma unroll
    for (int a = 0; a < 4; a++) {
        const int o = (a & 1) * 256 + (a >> 1) * 1024;
        m |= deq_v4<CHECK>(v[a], __shfl_sync(0xffffffffu, zs, r0 + (a & 1) * 2 + (a >> 1) * 8), off, ((a & 1) ? d1 : d0) + o, ((a & 1) ? d0 : d1) + o) & (0x00010001u << a);
    }
    if (!CHECK) return true;
    m = ((m | m >> 16) & 15) << (r0 & 1) * 4;
    if (!v_token_ok(zs, off)) m |= 256;
    return __reduce_or_sync(0xffffffffu, m) == 255;
}
__device__ __forceinline__ void start_k(const Params& P, int head, int key0, uint8_t* img, int w, int lane, uint64_t pol, float koff) {
    const int hw = lane >> 4, l16 = lane & 15;
    const uint8_t* src = (const uint8_t*)(P.qk + ((size_t)head * SEQ + key0) * DH) + (uint32_t)(w * 3072 + hw * 768 + l16 * 16);
    const size_t so = ((size_t)head * 32 + (key0 >> 6)) * DH + l16 * 4;
    int4 v[3][2]; uint2 z[3], sc[3];
#pragma unroll
    for (int c = 0; c < 3; c++) {
        v[c][0] = ldg_stream(src + c * 256, pol); v[c][1] = ldg_stream(src + 1536 + c * 256, pol);
        z[c] = __ldg((const uint2*)(P.kz + so + c * 64)); sc[c] = __ldg((const uint2*)(P.ks + so + c * 64));
    }
#pragma unroll
    for (int c = 0; c < 3; c++) {
        const KScale f(sc[c], z[c], koff);
#pragma unroll
        for (int a = 0; a < 2; a++) {
            const int row = (key0 & 127) + 4 * w + 2 * a + hw;
            *(uint2*)(img + c * SUB + row * 128 + (((l16 >> 1) ^ (row & 7)) << 4) + (l16 & 1) * 8) = f(v[c][a]);
        }
    }
}
template <bool OFFSET>
__device__ __forceinline__ bool start_v(const Params& P, int head, int key0, uint8_t* img, int w, int lane, uint64_t pol) {
    const int hw = lane >> 4, l16 = lane & 15, g = (l16 >> 3) * 4 + (l16 & 1);
    const uint8_t* src = (const uint8_t*)(P.qv + ((size_t)head * SEQ + key0) * DH) + (uint32_t)(w * 1536 + hw * 768 + l16 * 16);
    int4 v[3];
#pragma unroll
    for (int c = 0; c < 3; c++) v[c] = ldg_stream(src + c * 256, pol);
    const uint32_t zs = load_vzs(P, (size_t)head * SEQ + key0 + 2 * w + hw);
    const uint32_t off = OFFSET ? v_offset(P, head, lane) : 0;
    const int row = (key0 & 127) + 2 * w + hw;
    uint32_t far = 0;
#pragma unroll
    for (int c = 0; c < 3; c++) {
        uint8_t* d = img + c * SUB + row * 128 + ((l16 >> 1) & 3) * 4;
        far |= deq_v4<OFFSET>(v[c], zs, off, d + ((g ^ (row & 7)) << 4), d + ((g ^ 2 ^ (row & 7)) << 4));
    }
    if (!OFFSET) return true;
    const uint32_t b = __ballot_sync(0xffffffffu, far != 0);
    return (b & 0xffff) && (b >> 16) && __all_sync(0xffffffffu, v_token_ok(zs, off));
}

__device__ __forceinline__ void proxy_fence_global() { asm volatile("fence.proxy.async.global;" ::: "memory"); }
__device__ __forceinline__ void publish(unsigned long long* flag, int byte, uint32_t val) {
    proxy_fence_global();
    asm volatile("st.release.gpu.global.u8 [%0], %1;" ::"l"((uint8_t*)flag + byte), "r"(val) : "memory");
}
__device__ __forceinline__ void wait_flag(const unsigned long long* f, uint32_t redo) {
    uint32_t n = 0;
    while (true) {
        unsigned long long v;
        asm volatile("ld.acquire.gpu.global.u64 %0, [%1];" : "=l"(v) : "l"(f) : "memory");
        if (__all_sync(0xffffffffu, (v & TILE_READY) == TILE_READY)) {
            if (redo && (((uint32_t)v | (uint32_t)(v >> 32)) & FLAG_VBAD)) set_flag(redo);
            __syncwarp();
            break;
        }
        if (++n > SPIN_LIMIT) __trap();
        __nanosleep(20);
    }
}
__device__ __forceinline__ void wait_flags(const unsigned long long* f, uint32_t skip, uint32_t koff, uint32_t redo) {
    constexpr uint32_t READY = (uint32_t)TILE_READY;
    uint32_t n = 0;
    while (true) {
        uint32_t a, b, c, d;
        asm volatile("ld.acquire.gpu.global.v4.u32 {%0, %1, %2, %3}, [%4];" : "=r"(a), "=r"(b), "=r"(c), "=r"(d) : "l"(f) : "memory");
        if (__all_sync(0xffffffffu, (a & b & ((c & d) | skip) & READY) == READY)) {
            if ((a | b | c | d) != READY) {
                if (koff) asm volatile("st.shared.v4.u32 [%0], {%1, %1, %1, %1};" ::"r"(koff), "r"(0) : "memory");
                if ((c | d) & ~skip & FLAG_VBAD) set_flag(redo);
            }
            __syncwarp();
            break;
        }
        if (++n > SPIN_LIMIT) __trap();
        __nanosleep(20);
    }
}
__device__ __forceinline__ uint32_t atom_add0(const void* p, uint32_t x) {
    uint32_t v;
    asm volatile("{\n.reg .pred p;\n.reg .u32 l;\nmov.u32 l, %laneid;\nsetp.eq.u32 p, l, 0;\nmov.u32 %0, 0;\n"
                 "@p atom.relaxed.gpu.global.add.u32 %0, [%1], %2;\n}\n" : "=r"(v) : "l"(p), "r"(x) : "memory");
    return v;
}
__device__ __forceinline__ uint32_t clock_after(uint32_t v) {
    uint32_t c;
    asm volatile("{\n.reg .u32 t;\nshfl.sync.idx.b32 t, %1, 0, 31, 0xffffffff;\nmov.u32 %0, %clock;\nadd.u32 %0, %0, t;\n}\n" : "=r"(c) : "r"(v) : "memory");
    return c;
}
__device__ __forceinline__ void wait_until(uint32_t c0, uint32_t clks) {
    while (__shfl_sync(0xffffffffu, (uint32_t)clock() - c0, 0) < clks) __nanosleep(32);
}
__device__ __forceinline__ void cluster_arrive() { asm volatile("barrier.cluster.arrive.relaxed.aligned;" ::: "memory"); }
__device__ __forceinline__ void cluster_wait() { asm volatile("barrier.cluster.wait.acquire.aligned;" ::: "memory"); }

struct Softmax {
    float m0, m1, l0, l1, a0, a1;
    bool fast, resc;

    template <bool first> __device__ __forceinline__ void run(float (&s)[64]) {
        if (first) { l0 = 0.f; l1 = 0.f; }
        if (fast) {
            resc = false;
#pragma unroll
            for (int j = 0; j < 64; j++) s[j] = ex2(s[j]);
            float x0 = s[0], x1 = s[2], y0 = s[1], y1 = s[3];
#pragma unroll
            for (int j = 1; j < 16; j++) { x0 += s[4 * j]; y0 += s[4 * j + 1]; x1 += s[4 * j + 2]; y1 += s[4 * j + 3]; }
            l0 += x0 + y0; l1 += x1 + y1;
        } else {
            float x0 = fmaxf(s[0], s[1]), x1 = fmaxf(s[2], s[3]), y0 = fmaxf(s[4], s[5]), y1 = fmaxf(s[6], s[7]);
#pragma unroll
            for (int j = 2; j < 16; j += 2) {
                x0 = fmaxf(x0, fmaxf(s[4 * j], s[4 * j + 1]));     x1 = fmaxf(x1, fmaxf(s[4 * j + 2], s[4 * j + 3]));
                y0 = fmaxf(y0, fmaxf(s[4 * j + 4], s[4 * j + 5])); y1 = fmaxf(y1, fmaxf(s[4 * j + 6], s[4 * j + 7]));
            }
            x0 = fmaxf(x0, y0); x1 = fmaxf(x1, y1);
            x0 = fmaxf(x0, __shfl_xor_sync(0xffffffffu, x0, 1));
            x1 = fmaxf(x1, __shfl_xor_sync(0xffffffffu, x1, 1));
            x0 = fmaxf(x0, __shfl_xor_sync(0xffffffffu, x0, 2));
            x1 = fmaxf(x1, __shfl_xor_sync(0xffffffffu, x1, 2));
            if (first) {
                a0 = 0.f; a1 = 0.f;
                resc = false;
            } else {
                x0 = fmaxf(x0, m0); x1 = fmaxf(x1, m1);
                a0 = ex2(m0 - x0); a1 = ex2(m1 - x1);
                resc = __any_sync(0xffffffffu, x0 != m0 || x1 != m1);
            }
            m0 = x0; m1 = x1;
            float r0 = 0.f, r1 = 0.f;
#pragma unroll
            for (int j = 0; j < 16; j++) {
                s[4 * j] = ex2(s[4 * j] - x0); s[4 * j + 1] = ex2(s[4 * j + 1] - x0);
                s[4 * j + 2] = ex2(s[4 * j + 2] - x1); s[4 * j + 3] = ex2(s[4 * j + 3] - x1);
                r0 += s[4 * j] + s[4 * j + 1];
                r1 += s[4 * j + 2] + s[4 * j + 3];
            }
            l0 = fmaf(l0, a0, r0); l1 = fmaf(l1, a1, r1);
        }
    }
    __device__ __forceinline__ void pack(const float (&s)[64], uint32_t (&p)[32]) {
#pragma unroll
        for (int j = 0; j < 32; j++) p[j] = pack_bf16(s[2 * j], s[2 * j + 1]);
    }
    __device__ __forceinline__ void rescale(float (&o)[96]) {
        if (resc) {
#pragma unroll
            for (int i = 0; i < 24; i++) { o[4 * i] *= a0; o[4 * i + 1] *= a0; o[4 * i + 2] *= a1; o[4 * i + 3] *= a1; }
        }
    }
    __device__ __forceinline__ void finish(float& i0, float& i1, uint32_t redo) {
        float f0 = l0 + __shfl_xor_sync(0xffffffffu, l0, 1), f1 = l1 + __shfl_xor_sync(0xffffffffu, l1, 1);
        f0 += __shfl_xor_sync(0xffffffffu, f0, 2); f1 += __shfl_xor_sync(0xffffffffu, f1, 2);
        i0 = rcp(f0 * __uint_as_float((127 + VEXP) << 23)); i1 = rcp(f1 * __uint_as_float((127 + VEXP) << 23));
        constexpr uint32_t lo = (127 - 40) << 23, span = 80 << 23;
        if (__any_sync(0xffffffffu, __float_as_uint(f0) - lo > span || __float_as_uint(f1) - lo > span)) { fast = false; set_flag(redo); }
    }
};
__device__ __forceinline__ void q_first(const CUtensorMap* qmap, uint32_t dst, int row0, uint32_t bar) {
#pragma unroll
    for (int w = 0; w < 4; w++) { mbar_expect_tx(bar, 6144); tma_load_q16(dst + w * 6144, qmap, (row0 >> 3) + 2 * w, bar); }
}

__global__ void __cluster_dims__(CLUSTER, 1, 1) __launch_bounds__(512, 1)
kvq_attn_kernel(const __grid_constant__ Params P, const __grid_constant__ CUtensorMap qmap) {
    extern __shared__ uint8_t smem_raw[];
    const uint32_t sb = (smem_u32(smem_raw) + 1023) & ~1023u;
    const int tid = threadIdx.x;
    if (tid == 128) {
        const uint32_t b = blockIdx.x;
        const uint8_t* src = *(const uint8_t* const*)((const uint8_t*)&P.qk + (b & 8)) + ((b >> 4) * (SEQ / 16) + (b & 7)) * (16 * DH * 4);
        asm volatile("{\n.reg .pred p;\nsetp.eq.u32 p, %1, 0;\ncp.async.bulk.prefetch.L2.global [%0], 12288;\n"
                     "@p cp.async.bulk.prefetch.L2.global [%0 + 98304], 12288;\n}\n" ::"l"(src), "r"(b & 8) : "memory");
    }
    const int warp = __shfl_sync(0xffffffffu, tid >> 5, 0), wg = warp >> 2;
    const uint32_t clk0 = (uint32_t)clock();
    auto role = [&]() { mbar_wait_sleep(sb + B_ROLE, 0); return __shfl_sync(0xffffffffu, lds_u32(sb + SM_ROLE), 0); };

    if (tid == 160) { TS(0, 70); }
    if (wg == 0 || wg == 3) {
        const int lane = tid & 31;
        const uint32_t crank = blockIdx.x % CLUSTER;
        uint32_t* state = (uint32_t*)(P.pages + CTL_STATE);
        uint8_t* probe = P.pages + ctl_off(warp & 7) + CTL_PROBE + (blockIdx.x >> 1) * 32;
        uint32_t v0 = 0;
        if (crank == 0) {
            asm volatile("{\n.reg .pred p;\nsetp.lt.u32 p, %2, 2;\n@p st.global.v4.u32 [%0], {%1, %1, %1, %1};\n}\n"
                         ::"l"(probe + lane * 16), "r"(0), "r"(lane) : "memory");
            v0 = atom_add0(probe, 0);
        } else if (warp > 3) {
            const uint32_t n = warp & 2 ? 512 : 1536;
            l2_prefetch((const uint8_t*)(&P.ks)[warp & 3] + (blockIdx.x >> 1) * n, n);
        } else {
            asm volatile("{\n.reg .pred p;\nsetp.eq.u32 p, %4, 0;\n@p st.relaxed.gpu.global.v4.u32 [%0], {%1, %2, %3, %3};\n}\n"
                         ::"l"(state + (lane & 1) * 4), "r"(ST_OPEN), "r"(PAR_OPEN), "r"(0), "r"(((tid ^ 64) | blockIdx.x) >> 1) : "memory");
        }
        if (tid == 0) {
            asm volatile("prefetch.tensormap [%0];" ::"l"(&qmap) : "memory");
            for (int i = 0; i < KSLOTS; i++) { mbar_init(sb + B_KFULL + 8 * i, 1); mbar_init(sb + B_KEMPTY + 8 * i, 2 * CLUSTER); }
            for (int i = 0; i < 2; i++) {
                mbar_init(sb + B_VFULL + 8 * i, 1); mbar_init(sb + B_VEMPTY + 8 * i, 2 * CLUSTER);
                mbar_init(sb + B_QFULL + 8 * i, 4);
            }
            for (int i = 0; i < 8; i++) mbar_init(sb + B_UNIT + 8 * i, 6);
            mbar_init(sb + B_ROLE, 1); mbar_expect_tx(sb + B_ROLE, 4);
            for (int i = 0; i < 4; i++) asm volatile("st.shared.v4.f32 [%0], {%1, %2, %2, %2};" ::"r"(sb + SM_OFF + 16 * i), "f"(KOFF), "f"(0.f) : "memory");
            asm volatile("st.shared.v4.u32 [%0], {%1, %2, %2, %2};" ::"r"(sb + SM_PROG), "r"(-64), "r"(0) : "memory");
            asm volatile("fence.acq_rel.cta;" ::: "memory");
            asm volatile("fence.mbarrier_init.release.cluster;" ::: "memory");
            asm volatile("fence.proxy.async.shared::cta;" ::: "memory");
        }
        __syncwarp();
        cluster_arrive();
        asm volatile("setmaxnreg.dec.sync.aligned.u32 32;");
        auto pf_scales = [&](int item, int id) {
            const size_t h = item * NGROUP + (id >> 4);
            const int r = id & 15;
            l2_prefetch(P.ks + h * 32 * DH + r * 384, 768); l2_prefetch(P.kz + h * 32 * DH + r * 384, 768);
            l2_prefetch(P.vs + h * SEQ + r * 128, 256);     l2_prefetch(P.vz + h * SEQ + r * 128, 256);
        };
        if (crank == 0) {
            asm volatile("bar.sync 5, %0;" ::"r"(256 + __shfl_sync(0xffffffffu, v0, 0)) : "memory");
            const uint32_t c0 = clock_after(v0);
            const uint32_t c1 = clock_after(atom_add0(probe, 0));
            asm volatile("st.shared.u32 [%0], %1;" ::"r"(sb + SM_LAT + (warp & 7) * 4), "r"(c1 - c0) : "memory");
            cluster_wait();
            if (warp != 1) bar_arrive(4);
            else {
                bar_sync(4);
                uint2 a;
                asm volatile("ld.shared.v2.u32 {%0,%1}, [%2];" : "=r"(a.x), "=r"(a.y) : "r"(sb + SM_LAT + (lane & 3) * 8) : "memory");
                uint32_t par = __ballot_sync(0xffffffffu, a.x > a.y) & 15, par0 = 0;
                const uint32_t side = par & 1;
                par = (par ^ (side * 15)) | 16;
                uint32_t n = 0;
#pragma unroll 1
                for (int i = 0; !(n & ST_OPEN) || !par0; i++) {
                    if (i >> 16) __trap();
                    asm volatile("{\n.reg .pred p, q;\nsetp.eq.u32 p, %5, 0;\nsetp.ge.and.s32 q, %0, 0, p;\n"
                                 "@p atom.relaxed.gpu.global.cas.b32 %1, [%2 + 4], %6, %4;\n"
                                 "@q atom.relaxed.gpu.global.add.u32 %0, [%2], %3;\n}\n"
                                 : "+r"(n), "+r"(par0) : "l"(state), "r"(side ? 256 : 1), "r"(par), "r"(lane), "n"(PAR_OPEN) : "memory");
                    n = __shfl_sync(0xffffffffu, n, 0); par0 = __shfl_sync(0xffffffffu, par0, 0);
                }
                if (par0 != PAR_OPEN) par = par0;
                n = side ? 63 - (n >> 8 & 255) : n & 255;
                const uint32_t up = n >> 5, k = up ? 63 - n : n;
                const uint32_t id = (((k >> 3) * 2 + ((par >> (k >> 3) & 1) ^ up)) * 8 + (k & 7)) * CLUSTER;
                asm volatile("{\n.reg .u32 a;\n.reg .pred p;\nsetp.lt.u32 p, %1, 2;\nmapa.shared::cluster.u32 a, %0, %3;\n"
                             "@p st.async.weak.shared::cluster.mbarrier::complete_tx::bytes.u32 [a + 8], %2, [a];\n}\n"
                             ::"r"(sb + B_ROLE), "r"(lane), "r"(id + lane), "r"(lane & 1) : "memory");
            }
        } else {
#pragma unroll 1
            for (int i = 0; i < (warp == 3 ? 12 : 0); i++) {
                wait_until(clk0, Q_T0 + i * Q_DT);
                l2_prefetch(P.q + (size_t)((blockIdx.x - (i & 1)) * 128 * DH + (i >> 1) * 4096), 8192);
            }
            cluster_wait();
        }
        const int bid = role(), grp = bid >> 4, rk = bid & 15;
        uint8_t* ring = P.pages + (grp >> 1) * PAGE;
        unsigned long long* flags = (unsigned long long*)(P.pages + ctl_off(grp));
        if (warp == 0) {
            wait_until(clk0, POLL_T);
            __syncwarp();
            constexpr int VSEP = 8;
            uint32_t kslot = 0, kphase = 1;
            auto load_k = [&](int t, int c) {
                if (t >= TOTAL) return;
                if (c == 0) {
                    if (t > 1) { TP(5, t); }
                    if (t == 0) wait_flag(flags + CTL_PROBE / 8 + (grp * 8 + (lane & 3)) * 4, 0);
                    else if (t > 1) wait_flags(flags + 2 * t, t > VSEP ? 0 : ~0u, (t & 15) == 13 ? sb + SM_OFF + (t >> 4) * 16 + 16 : 0, sb + SM_REDO + (t - 1 >> 4));
                    TP(6, t);
                    const int prog = t + (int)(0x94000000u >> (t & 15) * 2 & 3);
                    if (lane == 0) asm volatile("red.release.cta.shared.max.s32 [%0], %1;" ::"r"(sb + SM_PROG), "r"(prog) : "memory");
                }
                mbar_wait_sleep(sb + B_KEMPTY + 8 * kslot, kphase);
                bulk_load_mc<1>(sb + SM_K + kslot * SUB + crank * 8192, ring + (ring_off(grp, t, crank) + c * SUB), sb + B_KFULL + 8 * kslot);
                if (++kslot == KSLOTS) { kslot = 0; kphase ^= 1; }
            };
            auto load_v = [&](int t) {
                if (t >= TOTAL) return;
                if (t < 8) { TP(5, 64 + t); }
                if (t == 0) wait_flag(flags + CTL_PROBE / 8 + (grp * 8 + 4 + (lane & 3)) * 4, sb + SM_REDO);
                else if (((t + 1) & (TOTAL - 1)) <= VSEP) wait_flag(flags + 2 * t + 3, sb + SM_REDO + (t >> 4));
                if (t < 8) { TP(6, 64 + t); }
                const int s = t & 1;
                mbar_wait_sleep(sb + B_VEMPTY + 8 * s, ((t >> 1) & 1) ^ 1);
                bulk_load_mc<3>(sb + SM_V + s * TILE + crank * 8192, ring + ring_off(grp, t, 2 + crank), sb + B_VFULL + 8 * s);
            };
            load_k(0, 0); load_k(0, 1); load_k(0, 2);
            if (lane == 0) q_first(&qmap, sb + SM_Q + 24576, bid * 128 + 64, sb + B_QFULL + 8);
            __syncwarp();
            load_k(1, 0); load_k(1, 1); load_v(0);
#pragma unroll 1
            for (int i = -1; i < TOTAL - 2; i++) {
                if ((i & 15) == 7 && i < TOTAL - 16) pf_scales((i >> 4) + 1, bid);
                if ((i & 15) >= QPF && (i & 15) < QPF + 4 && i < TOTAL - 16)
                    l2_prefetch(P.q + (size_t)(((i >> 4) + 1) * NCTA + bid) * 128 * DH + ((i & 15) - QPF) * 32 * DH, 12288);
                load_k(i + 2, 2); load_k(i + 3, 0); load_k(i + 3, 1);
                load_v(i + 2);
            }
            unsigned int old = 0;
            if (lane == 0) asm volatile("atom.acq_rel.gpu.global.add.u32 %0, [%1], 1;" : "=r"(old) : "l"(state + 8) : "memory");
            if (__shfl_sync(0xffffffffu, old, 0) == NCTA - 1) {
                __syncwarp();
#pragma unroll 1
                for (int g = 0; g < NGROUP; g++) {
                    uint4* c = (uint4*)(P.pages + ctl_off(g));
                    c[1 + lane] = c[33 + lane] = c[CTL_PROBE / 16 + g * 16 + (lane & 15)] = make_uint4(0, 0, 0, 0);
                }
                if (lane < 3) ((uint4*)state)[lane] = make_uint4(0, 0, 0, 0);
            }
        } else {
            const int u = rk & 7;
            const bool isV = rk >= 8;
            const int tfirst = isV ? 1 : 2;
            const int* base = isV ? P.qv : P.qk;
            auto unit_ptr = [&](int t) { return base + ((size_t)((t >> 4) * NGROUP + grp) * SEQ + (t & 15) * 128 + u * 16) * DH; };
            if (warp == 1) {
#pragma unroll 1
                for (int i = 0; i < PFD; i++) {
                    wait_until(clk0, (isV ? PF_TV : PF_TK) + i * PF_DT);
                    l2_prefetch(unit_ptr(tfirst + i), 12288);
                }
#pragma unroll 1
                for (int t = tfirst; t < TOTAL; t++) {
                    mbar_wait_sleep(sb + B_UNIT + 8 * (t & 7), ((t - tfirst) >> 3) & 1);
                    if (t + PFD < TOTAL) l2_prefetch(unit_ptr(t + PFD), 12288);
                    if (lane == 0) {
                        TP(3, t);
                        publish(flags + 2 * t + (isV ? 3 : 0), u, 1 | lds_u32(sb + SM_QBIG) | (lds_u32(sb + SM_VBAD) >> (t >> 4) * 8 & 4));
                        TP(4, t);
                    }
                    __syncwarp();
                    if ((t & 15) == 11 && t < TOTAL - 16) put_v_offset(sb + SM_OFF + (t >> 4) * 16 + 16, v_offset(P, ((t >> 4) + 1) * NGROUP + grp, lane));
                }
            } else {
                const uint64_t pol = policy_evict_first();
                const int pw = warp < 4 ? warp - 2 : warp - 10, c = pw >> 1, h = pw & 1;
                const int hw = lane >> 4, l16 = lane & 15;
                const uint32_t soff = h * 3072 + c * 256 + hw * 768 + l16 * 16;
                const uint32_t doff = (u & 3) * 2048 + c * SUB + h * 512 + hw * 128 +
                                      (isV ? ((((l16 >> 3) * 4 + (l16 & 1)) ^ hw ^ (4 * h)) << 4) + ((l16 >> 1) & 3) * 4
                                           : (((l16 >> 1) ^ hw ^ (4 * h)) << 4) + (l16 & 1) * 8);
                put_v_offset(sb + SM_OFF, v_offset(P, grp, lane));
                wait_until(clk0, isV ? DQ_TV : DQ_TK);
#pragma unroll 1
                for (int t = tfirst; t < TOTAL; t++) {
                    uint32_t n = 0;
                    while (true) {
                        int prog;
                        asm volatile("ld.acquire.cta.shared.u32 %0, [%1];" : "=r"(prog) : "r"(sb + SM_PROG) : "memory");
                        if (prog + LEAD >= t + (isV ? 1 : 0)) break;
                        if (++n > SPIN_LIMIT) __trap();
                        __nanosleep(WPOLL);
                    }
                    if (lane == 0 && pw == 0) { TP(2, t); }
                    const int head = (t >> 4) * NGROUP + grp;
                    const uint8_t* src = (const uint8_t*)unit_ptr(t) + soff;
                    uint8_t* slot = ring + ring_off(grp, t, rk >> 2);
                    if (isV) {
                        const size_t key0 = (size_t)head * SEQ + (t & 15) * 128 + u * 16;
                        const uint32_t voff = sb + SM_OFF + (t >> 4) * 16 + 8;
                        if (c != 0) part_v<false>(P, src, key0, h, slot, doff, pol, voff);
                        else if (!part_v<true>(P, src, key0, h, slot, doff, pol, voff)) { set_flag(sb + SM_QBIG); set_vbad(sb + SM_VBAD + (t >> 4)); }
                    } else {
                        const size_t so = ((size_t)head * 32 + (t & 15) * 2 + (u >> 2)) * DH + c * 64;
                        part_k(P, src, (const uint8_t*)(P.ks + so) + (uint32_t)((lane & 15) * 8), (const uint8_t*)(P.kz + so) + (uint32_t)((lane & 15) * 8),
                               slot, doff, pol, sb + SM_OFF + (t >> 4) * 16);
                    }
                    __syncwarp();
                    if (lane == 0) mbar_arrive(sb + B_UNIT + 8 * (t & 7));
                    const int b = ((t & 15) - (isV ? 9 : 10)) * 6 + pw;
                    if (b >= 0 && b < 16) {
                        mbar_wait(sb + B_QFULL + (b & 8), (t >> 4) & 1);
                        if (q8_big(sb + SM_Q + b * 3072)) {
                            set_flag(sb + SM_QBIG);
                            if (lds_u32(sb + SM_OFF + (t >> 4) * 16)) set_flag(sb + SM_REDO + (t >> 4));
                        }
                        __syncwarp();
                    }
                }
            }
        }
        __syncwarp();
        cluster_arrive();
        cluster_wait();
    } else {
        const int cw = wg - 1, t128 = tid & 127, lane = tid & 31;
        cluster_arrive();
        {
            const int grp = blockIdx.x >> 4, rk = blockIdx.x & 15;
            uint8_t* ring = P.pages + (grp >> 1) * PAGE - (rk & 4) * 2048;
            const uint64_t pol = policy_evict_first();
            const int key0 = cw * 128 + (rk & 7) * 16;
            if (t128 == 0) { TS(cw, 71); }
            bool good = true;
            if (rk >= 8) good = start_v<true>(P, grp, (rk & 7) * 16, ring + ring_off(grp, 0, rk >> 2), (tid >> 5) - 4, lane, pol);
            else start_k(P, grp, key0, ring + ring_off(grp, cw, rk >> 2), t128 >> 5, lane, pol, KOFF);
            if (t128 == 0) { TS(cw, 73); }
            cluster_wait();
            if (!good) set_vbad(sb + SM_VBAD);
            bar_sync(3);
            if (t128 == 0) { TS(cw, 74); }
            if (tid == 128) {
                proxy_fence_global();
                asm volatile("fence.release.gpu;" ::: "memory");
                mbar_wait(sb + B_ROLE, 0);
                asm volatile("st.relaxed.gpu.global.u32 [%0], %1;"
                             ::"l"(P.pages + ctl_off(grp) + CTL_PROBE + (blockIdx.x >> 1) * 32 + (rk & 1) * 4), "r"((uint32_t)TILE_READY | (lds_u32(sb + SM_VBAD) & 4)) : "memory");
                q_first(&qmap, sb + SM_Q, lds_u32(sb + SM_ROLE) * 128, sb + B_QFULL);
                asm volatile("red.release.cta.shared.max.s32 [%0], %1;" ::"r"(sb + SM_PROG), "r"(0) : "memory");
            }
            if (t128 == 0) { TS(cw, 75); }
            __syncwarp();
        }
        asm volatile("setmaxnreg.inc.sync.aligned.u32 224;");
        const int bid = role();
        float o[96], s[64];
        uint32_t p[32];
        Softmax sm;
        sm.fast = true; sm.m0 = 0.f; sm.m1 = 0.f; sm.a0 = 0.f; sm.a1 = 0.f;
        uint32_t kslot = 0, kphase = 0;
        const uint32_t sl = sb & 0x3FFFF;
        const uint32_t qdesc = ((sl + SM_Q + cw * 24576) >> 4) | (1u << 16);
        const uint32_t kdesc0 = ((sl + SM_K) >> 4) | (1u << 16), vdesc0 = ((sl + SM_V) >> 4) | ((SUB >> 4) << 16);
        uint32_t rbar;
        asm volatile("{\n.reg .pred p;\nmapa.shared::cluster.u32 %0, %1, %2;\nsetp.ne.u32 p, %3, 0;\n@p mov.u32 %0, 0;\n}\n"
                     : "=r"(rbar) : "r"(sb + SM_BAR), "r"((t128 >> 5) % CLUSTER), "r"(t128 & ~(32 * (CLUSTER - 1))));
        auto release = [&](uint32_t off) {
            asm volatile("{\n.reg .pred p;\n.reg .u32 a;\nsetp.ne.u32 p, %0, 0;\nadd.u32 a, %0, %1;\n"
                         "@p mbarrier.arrive.shared::cluster.b64 _, [a];\n}\n" ::"r"(rbar), "r"(off) : "memory");
        };
        constexpr uint32_t OKE = B_KEMPTY - SM_BAR, OVE = B_VEMPTY - SM_BAR;
        const int w8 = __shfl_sync(0xffffffffu, (tid >> 5) - 4, 0);
        auto next_q = [&](int item) {
            asm volatile("{\n.reg .pred p;\nelect.sync _|p, 0xffffffff;\n"
                         "@p mbarrier.arrive.expect_tx.shared::cta.b64 _, [%2], 6144;\n"
                         "@p cp.async.bulk.tensor.4d.shared::cluster.global.mbarrier::complete_tx::bytes [%0], [%1, {%3, %3, %3, %4}], [%2];\n}\n"
                         ::"r"(sb + SM_Q + w8 * 6144), "l"(&qmap), "r"(sb + B_QFULL + 8 * cw), "r"(0), "r"((item * NCTA + bid) * 16 + w8 * 2) : "memory");
        };
        auto k_next = [&]() { if (++kslot == KSLOTS) { kslot = 0; kphase ^= 1; } };
        auto k_wait = [&]() { mbar_wait(sb + B_KFULL + 8 * kslot, kphase); };
        auto qk_chunk = [&](int c) {
            const uint32_t kd = kdesc0 + kslot * (SUB >> 4);
#pragma unroll
            for (int k = 0; k < 4; k++) wgmma_ss_n128(s, qdesc + c * 64 + k * 2, kd + k * 2, (c | k) != 0);
            wg_commit();
        };
        auto pv_half = [&](uint32_t vd, int h, int acc) {
#pragma unroll
            for (int k = 4 * h; k < 4 * h + 4; k++)
                wgmma_rs_n192_tb(o, p[4 * k], p[4 * k + 1], p[4 * k + 2], p[4 * k + 3], vd + k * 128, k == 0 ? acc : 1);
            wg_commit();
        };
        auto out_ptr = [&](int item) {
            const uint32_t tl = threadIdx.x & 127;
            __nv_bfloat16* d = P.out + (size_t)((item * NCTA + bid) * 128 + cw * 64) * DH +
                               (uint32_t)(((tl >> 5) * 16 + ((tl & 31) >> 2)) * DH + (tl & 3) * 8);
            asm volatile("" : "+l"(d));
            return d;
        };
        auto out_word = [&](int k, float i0, float i1, float c) {
            const int b = 16 * (k >> 1) + 2 * (k & 1);
            const float i = (k & 1) ? i1 : i0;
            return make_uint4(pack_bf16(fmaf(o[b], i, c), fmaf(o[b + 1], i, c)), pack_bf16(fmaf(o[b + 8], i, c), fmaf(o[b + 9], i, c)),
                              pack_bf16(fmaf(o[b + 4], i, c), fmaf(o[b + 5], i, c)), pack_bf16(fmaf(o[b + 12], i, c), fmaf(o[b + 13], i, c)));
        };
        auto v_back = [&](int item) { return __uint_as_float(lds_u32(sb + SM_OFF + item * 16 + 12)); };
        auto put_word = [&](__nv_bfloat16* d, int k, uint4 w) { __stcs((uint4*)(d + (k & 1) * 8 * DH + (k >> 1) * 32), w); };
        auto store_o = [&](__nv_bfloat16* d, float i0, float i1, float c, int n) {
#pragma unroll
            for (int k = 0; k < n; k++) put_word(d, k, out_word(k, i0, i1, c));
        };

#pragma unroll
        for (int i = 0; i < 96; i++) asm volatile("" : "=f"(o[i]));
        if (cw == 0) bar_arrive(1);

        if (t128 == 0) { TS(cw, 77); }
        mbar_wait(sb + B_QFULL + 8 * cw, 0);
        if (t128 == 0) { TS(cw, 78); }
        k_wait();
        if (t128 == 0) { TS(cw, 79); }
        bar_sync(1 + cw);
        wg_fence();
        qk_chunk(0); k_next(); k_wait(); qk_chunk(1); k_next(); k_wait(); qk_chunk(2); k_next();
        bar_arrive(1 + (cw ^ 1));
        wg_wait<2>(); release(OKE); wg_wait<1>(); release(OKE + 8); wg_wait<0>(); release(OKE + 16);
        fence_regs(s);
        sm.run<true>(s);
        sm.pack(s, p);

        constexpr int NOW = 9;
        float i0, i1, vb;
        __nv_bfloat16* d;
        auto step = [&](int t, auto LAST, auto FIRST) {
            constexpr bool last = decltype(LAST)::value;
            constexpr bool first = decltype(FIRST)::value;
            const uint32_t vd = vdesc0 + (t & 1) * (TILE >> 4);
            uint4 w[12 - NOW];
            if (last) {
                d = out_ptr(t >> 4);
                sm.finish(i0, i1, sb + SM_REDO + (t >> 4));
                vb = v_back(t >> 4);
                mbar_wait(sb + B_QFULL + 8 * cw, ((t + 1) >> 4) & 1);
            }
            k_wait();
            bar_sync(1 + cw);
            TF(0);
            fence_regs(p);
            wg_fence();
            const uint32_t e0 = kslot; qk_chunk(0); k_next(); k_wait();
            const uint32_t e1 = kslot; qk_chunk(1); k_next(); k_wait();
            const uint32_t e2 = kslot; qk_chunk(2); k_next();
            TF(1);
            if (first) {
                fence_regs(o);
#pragma unroll
                for (int k = 0; k < 12 - NOW; k++) {
                    w[k] = out_word(NOW + k, i0, i1, vb);
                    asm volatile("" : "+r"(w[k].x), "+r"(w[k].y), "+r"(w[k].z), "+r"(w[k].w));
                }
            } else sm.rescale(o);
            fence_regs(o);
            wg_wait<2>(); release(OKE + 8 * e0);
            TF(2);
            mbar_wait(sb + B_VFULL + 8 * (t & 1), (t >> 1) & 1);
            wg_fence();
            pv_half(vd, 0, !first && (last || t != 0));
            wg_wait<2>(); release(OKE + 8 * e1);
            pv_half(vd, 1, 1);
            bar_arrive(1 + (cw ^ 1));
            TF(3);
            wg_wait<2>(); release(OKE + 8 * e2);
            TF(4);
            if (!last && !first && (t & 15) == 14 && t < TOTAL - 2) next_q((t >> 4) + 1);
            fence_regs(s);
            sm.run<last>(s);
            fence_regs(s);
            TF(5);
            wg_wait<0>();
            release(OVE + 8 * (t & 1));
            if (first) {
#pragma unroll
                for (int k = 0; k < 12 - NOW; k++) put_word(d, NOW + k, w[k]);
            }
            fence_regs(o);
            if (last) store_o(d, i0, i1, vb, NOW);
            TF(6);
            sm.pack(s, p);
            fence_regs(p);
            TF(7);
        };
#pragma unroll 1
        for (int t = 0;;) {
#pragma unroll 1
            do { step(t, Flag<false>(), Flag<false>()); t++; } while ((t & 15) != 15);
            if (t == TOTAL - 1) break;
            step(t, Flag<true>(), Flag<false>());
            step(t + 1, Flag<false>(), Flag<true>());
            t += 2;
        }
        {
            constexpr int t = TOTAL - 1;
            const uint32_t vd = vdesc0 + (t & 1) * (TILE >> 4);
            d = out_ptr(3);
            TS(cw, 72);
            sm.rescale(o);
            sm.finish(i0, i1, sb + SM_REDO + 3);
            vb = v_back(3);
            mbar_wait(sb + B_VFULL + 8 * (t & 1), (t >> 1) & 1);
            bar_sync(1 + cw);
            fence_regs(o); fence_regs(p);
            wg_fence();
            pv_half(vd, 0, 1); pv_half(vd, 1, 1);
            bar_arrive(2 + cw);
            wg_wait<0>();
            TS(cw, 76);
            cluster_arrive();
            fence_regs(o);
            uint32_t x[12];
#pragma unroll
            for (int k = 0; k < 12; k++) {
                const uint4 w = out_word(k, i0, i1, k < 2 ? vb : __uint_as_float(__float_as_uint(vb) ^ (x[k - 2] & P.zero)));
                put_word(d, k, w);
                x[k] = w.w;
            }
        }
        if (cw == 0) bar_sync(3);
        uint32_t redo = lds_u32(sb + SM_REDO), qphase = 0;
        if (redo) bar_sync(4);
#pragma unroll 1
        for (int item = 0; redo; item++, redo >>= 8) {
            if (!(redo & 255)) continue;
            uint8_t* img = smem_raw + (sb - smem_u32(smem_raw));
            const uint64_t pol = policy_evict_first();
            const int head = item * NGROUP + (bid >> 4);
            next_q(item);
            sm.fast = false; sm.m0 = -INFINITY; sm.m1 = -INFINITY; sm.l0 = 0.f; sm.l1 = 0.f;
#pragma unroll 1
            for (int t = 0; t < 16; t++) {
#pragma unroll 2
                for (int a = 0; a < 4; a++) start_k(P, head, t * 128 + (2 * a + cw) * 16, img + SM_K, w8 & 3, lane, pol, 0.f);
#pragma unroll 4
                for (int a = 0; a < 8; a++) start_v<false>(P, head, t * 128 + a * 16, img + SM_V, w8, lane, pol);
                asm volatile("fence.proxy.async.shared::cta;" ::: "memory");
                bar_sync(3);
                mbar_wait(sb + B_QFULL + 8 * cw, qphase);
                wg_fence();
                kslot = 0; qk_chunk(0); kslot = 1; qk_chunk(1); kslot = 2; qk_chunk(2);
                wg_wait<0>();
                fence_regs(s);
                sm.run<false>(s);
                sm.pack(s, p);
                sm.rescale(o);
                fence_regs(o); fence_regs(p);
                wg_fence();
                pv_half(vdesc0, 0, t != 0); pv_half(vdesc0, 1, 1);
                wg_wait<0>();
                fence_regs(o);
                bar_sync(3);
            }
            sm.finish(i0, i1, sb + SM_REDO + 4);
            store_o(out_ptr(item), i0, i1, 0.f, 12);
            qphase ^= 1;
        }
        cluster_wait();
    }
}

typedef CUresult (*EncodeFn)(CUtensorMap*, CUtensorMapDataType, cuuint32_t, void*, const cuuint64_t*, const cuuint64_t*,
                             const cuuint32_t*, const cuuint32_t*, CUtensorMapInterleave, CUtensorMapSwizzle,
                             CUtensorMapL2promotion, CUtensorMapFloatOOBfill);

}

extern "C" void kernel_launch(void* const* d_in, const int* in_sizes, int n_in, void* d_out, int out_size) {
    cudaLaunchConfig_t cfg = {};
    cudaLaunchAttribute at[1];
    at[0].id = cudaLaunchAttributeClusterDimension;
    at[0].val.clusterDim.x = CLUSTER; at[0].val.clusterDim.y = 1; at[0].val.clusterDim.z = 1;
    cfg.attrs = at; cfg.numAttrs = 1;
    cfg.blockDim = dim3(512); cfg.dynamicSmemBytes = SMEM_BYTES; cfg.stream = cudaStreamPerThread;

    static EncodeFn encode = nullptr;
    static uintptr_t scratch;
    if (!encode) {
        void* fn = nullptr;
        cudaDriverEntryPointQueryResult st;
        cudaGetDriverEntryPoint("cuTensorMapEncodeTiled", &fn, cudaEnableDefault, &st);
        encode = (EncodeFn)fn;
        cudaFuncSetAttribute(kvq_attn_kernel, cudaFuncAttributeMaxDynamicSharedMemorySize, SMEM_BYTES);
        cudaGetSymbolAddress((void**)&scratch, g_scratch);
    }
    CUtensorMap qmap;
    const cuuint64_t gdim[4] = {64, 8, 3, (cuuint64_t)NH * SEQ / 8};
    const cuuint64_t gstride[3] = {DH * 2, 128, 8 * DH * 2};
    const cuuint32_t box[4] = {64, 8, 3, 2};
    const cuuint32_t estr[4] = {1, 1, 1, 1};
    encode(&qmap, CU_TENSOR_MAP_DATA_TYPE_BFLOAT16, 4, d_in[0], gdim, gstride, box, estr, CU_TENSOR_MAP_INTERLEAVE_NONE,
           CU_TENSOR_MAP_SWIZZLE_128B, CU_TENSOR_MAP_L2_PROMOTION_L2_128B, CU_TENSOR_MAP_FLOAT_OOB_FILL_NONE);
    Params P;
    P.q = (const __nv_bfloat16*)d_in[0];
    P.qk = (const int*)d_in[1]; P.qv = (const int*)d_in[2];
    P.ks = (const __nv_bfloat16*)d_in[3]; P.kz = (const __nv_bfloat16*)d_in[4];
    P.vs = (const __nv_bfloat16*)d_in[5]; P.vz = (const __nv_bfloat16*)d_in[6];
    P.out = (__nv_bfloat16*)d_out;
    P.pages = (uint8_t*)((scratch + PAGE - 1) & ~(uintptr_t)(PAGE - 1));
    P.zero = 0;
    cfg.gridDim = dim3(NCTA);
    cudaLaunchKernelEx(&cfg, kvq_attn_kernel, P, qmap);
}
```

```cpp
#include <cuda_runtime.h>
#include <cuda_bf16.h>
#include <cuda.h>
#include <stdint.h>

#define LEAD 2
#define Q_T0 1400
#define Q_DT 250
#define POLL_T 4100
#define PF_TK 4500
#define PF_TV 5100
#define PF_DT 1100
#define PFD 1
#define DQ_TK 5600
#define DQ_TV 5800
#define WPOLL 200
#define KOFF 1.25f
#define QPF 5
#define VEXP (-10)
#define HELP_T0 52000
#define VOFF 1.25f
#define TF0 29
#define SPIN_LIMIT (1u << 22)

namespace {

constexpr int CLUSTER = 2;
constexpr int NH = 32, SEQ = 2048, DH = 192;
constexpr int NGROUP = 8, GSIZE = 16, TOTAL = 64;
constexpr int NCTA = NGROUP * GSIZE;
constexpr int NHELP = 4;
constexpr uint32_t TILE = 128 * DH * 2;
constexpr uint32_t SUB = 16384;
constexpr int KSLOTS = 5;
constexpr int RING = 8;
static_assert(RING >= 2 * LEAD + 4, "a ring slot may only be rewritten after every CTA of the group has loaded it");

constexpr uint32_t SM_Q = 0;
constexpr uint32_t SM_K = 49152;
constexpr uint32_t SM_V = SM_K + KSLOTS * SUB;
constexpr uint32_t SM_BAR = SM_V + 2 * TILE;
constexpr uint32_t B_KFULL = SM_BAR, B_KEMPTY = B_KFULL + 8 * KSLOTS;
constexpr uint32_t B_VFULL = B_KEMPTY + 8 * KSLOTS, B_VEMPTY = B_VFULL + 16;
constexpr uint32_t B_QFULL = B_VEMPTY + 16;
constexpr uint32_t B_UNIT = B_QFULL + 16;
constexpr uint32_t B_ROLE = B_UNIT + 64, SM_ROLE = B_ROLE + 8;
constexpr uint32_t SM_LAT = B_ROLE + 16;
constexpr uint32_t SM_OFF = SM_LAT + 32;
constexpr uint32_t SM_PROG = SM_OFF + 80;
constexpr uint32_t SM_QBIG = SM_PROG + 4;
constexpr uint32_t SM_REDO = SM_PROG + 8;
constexpr uint32_t SM_VBAD = SM_PROG + 12;
constexpr uint32_t B_PART = SM_PROG + 16;
constexpr uint32_t B_PFLAG = SM_PROG + 32;
constexpr uint32_t B_HQ = SM_PROG + 16;
constexpr uint32_t SMEM_BYTES = SM_PROG + 64 + 1024;

constexpr uint32_t PAGE = 2u << 20, CTL_PART = 1088, CTL_STATE = 1536, CTL_PROBE = 2048;
__device__ __align__(1024) uint8_t g_scratch[(NGROUP / 2 + 1) * PAGE];
constexpr uint32_t PART_WG = 13 * 2048;
__device__ __align__(1024) uint8_t g_part[NCTA * 2 * PART_WG];
__device__ __forceinline__ uint32_t ring_off(int g, int t, int j) {
    const uint32_t s = t % RING, x = (j ^ (j >> 1) ^ (s >> 1) ^ g) & 1;
    return ((s * 4 + j) << 16) + (x ? 4096 : 12288);
}
__device__ __forceinline__ uint32_t ctl_off(int g) { return (g >> 1) * PAGE + ((g & 1) ? 53248 : 0); }

#define TR(ch, idx)
#define TP(ch, idx)
#define TRC(ch, idx)
#define TS(ch, idx)
#define TF(i)

constexpr uint32_t ST_OPEN = 0x80000000u, PAR_OPEN = 32;
constexpr unsigned long long TILE_READY = 0x0101010101010101ull;
constexpr uint32_t FLAG_VBAD = 0x04040404u;

__device__ __forceinline__ uint32_t smem_u32(const void* p) { return (uint32_t)__cvta_generic_to_shared(p); }
__device__ __forceinline__ void mbar_init(uint32_t bar, uint32_t cnt) {
    asm volatile("mbarrier.init.shared::cta.b64 [%0], %1;" ::"r"(bar), "r"(cnt) : "memory");
}
__device__ __forceinline__ void mbar_arrive(uint32_t bar) {
    asm volatile("mbarrier.arrive.shared::cta.b64 _, [%0];" ::"r"(bar) : "memory");
}
__device__ __forceinline__ void mbar_expect_tx(uint32_t bar, uint32_t bytes) {
    asm volatile("mbarrier.arrive.expect_tx.shared::cta.b64 _, [%0], %1;" ::"r"(bar), "r"(bytes) : "memory");
}
__device__ __forceinline__ void mbar_wait(uint32_t bar, uint32_t parity) {
    asm volatile("{\n.reg .pred p;\n.reg .u32 n;\n"
                 "mbarrier.try_wait.parity.shared::cta.b64 p, [%0], %1;\n@p bra DONE;\nmov.u32 n, 0;\n"
                 "LOOP:\nmbarrier.try_wait.parity.shared::cta.b64 p, [%0], %1;\n@p bra DONE;\n"
                 "add.u32 n, n, 1;\nsetp.lt.u32 p, n, %2;\n@p bra LOOP;\ntrap;\nDONE:\n}\n"
                 ::"r"(bar), "r"(parity), "n"(SPIN_LIMIT) : "memory");
}
__device__ __forceinline__ void mbar_wait_sleep(uint32_t bar, uint32_t parity) {
    asm volatile("{\n.reg .pred p;\n.reg .u32 n;\nmov.u32 n, 0;\n"
                 "LOOP:\nmbarrier.try_wait.parity.shared::cta.b64 p, [%0], %1, %3;\n@p bra DONE;\n"
                 "add.u32 n, n, 1;\nsetp.lt.u32 p, n, %2;\n@p bra LOOP;\ntrap;\nDONE:\n}\n"
                 ::"r"(bar), "r"(parity), "n"(1 << 18), "r"(10000) : "memory");
}
template <int N> __device__ __forceinline__ void bulk_load_mc(uint32_t dst, const void* src, uint32_t bar) {
    asm volatile("{\n.reg .pred p, q;\nelect.sync _|p, 0xffffffff;\nsetp.eq.and.u32 q, %5, 3, p;\n"
                 "@p mbarrier.arrive.expect_tx.shared::cta.b64 _, [%2], %4;\n"
                 "@p cp.async.bulk.shared::cluster.global.mbarrier::complete_tx::bytes.multicast::cluster [%0], [%1], 8192, [%2], %3;\n"
                 "@q cp.async.bulk.shared::cluster.global.mbarrier::complete_tx::bytes.multicast::cluster [%0 + 16384], [%1 + 16384], 8192, [%2], %3;\n"
                 "@q cp.async.bulk.shared::cluster.global.mbarrier::complete_tx::bytes.multicast::cluster [%0 + 32768], [%1 + 32768], 8192, [%2], %3;\n}\n"
                 ::"r"(dst), "l"(src), "r"(bar), "h"((uint16_t)((1 << CLUSTER) - 1)), "n"(N * SUB), "n"(N) : "memory");
}
__device__ __forceinline__ void tma_load_q16(uint32_t dst, const CUtensorMap* map, int g, uint32_t bar) {
    asm volatile("cp.async.bulk.tensor.4d.shared::cluster.global.mbarrier::complete_tx::bytes [%0], [%1, {%3, %3, %3, %4}], [%2];"
                 ::"r"(dst), "l"(map), "r"(bar), "r"(0), "r"(g) : "memory");
}
__device__ __forceinline__ void l2_prefetch(const void* p, uint32_t bytes) {
    asm volatile("{\n.reg .pred p;\nelect.sync _|p, 0xffffffff;\n@p cp.async.bulk.prefetch.L2.global [%0], %1;\n}\n" ::"l"(p), "r"(bytes) : "memory");
}
__device__ __forceinline__ uint64_t policy_evict_first() {
    uint64_t pol;
    asm volatile("createpolicy.fractional.L2::evict_first.b64 %0, 1.0;" : "=l"(pol));
    return pol;
}
__device__ __forceinline__ void wg_fence() { asm volatile("wgmma.fence.sync.aligned;" ::: "memory"); }
__device__ __forceinline__ void wg_commit() { asm volatile("wgmma.commit_group.sync.aligned;" ::: "memory"); }
template <int N> __device__ __forceinline__ void wg_wait() { asm volatile("wgmma.wait_group.sync.aligned %0;" ::"n"(N) : "memory"); }
__device__ __forceinline__ void bar_sync(int id) { asm volatile("bar.sync %0, 256;" ::"r"(id) : "memory"); }
__device__ __forceinline__ void bar_arrive(int id) { asm volatile("bar.arrive %0, 256;" ::"r"(id) : "memory"); }
__device__ __forceinline__ float ex2(float x) { float y; asm("ex2.approx.ftz.f32 %0, %1;" : "=f"(y) : "f"(x)); return y; }
__device__ __forceinline__ float rcp(float x) { float y; asm volatile("rcp.approx.ftz.f32 %0, %1;" : "=f"(y) : "f"(x)); return y; }
__device__ __forceinline__ uint32_t pack_bf16(float lo, float hi) {
    uint32_t r; asm("cvt.rn.bf16x2.f32 %0, %1, %2;" : "=r"(r) : "f"(hi), "f"(lo)); return r;
}
__device__ __forceinline__ uint32_t bf2_add(uint32_t a, uint32_t b) { uint32_t r; asm("add.rn.bf16x2 %0, %1, %2;" : "=r"(r) : "r"(a), "r"(b)); return r; }
__device__ __forceinline__ uint32_t bf2_sub(uint32_t a, uint32_t b) { uint32_t r; asm("sub.rn.bf16x2 %0, %1, %2;" : "=r"(r) : "r"(a), "r"(b)); return r; }
__device__ __forceinline__ uint32_t bf2_mul(uint32_t a, uint32_t b) { uint32_t r; asm("mul.rn.bf16x2 %0, %1, %2;" : "=r"(r) : "r"(a), "r"(b)); return r; }
__device__ __forceinline__ uint32_t bf2_fma(uint32_t a, uint32_t b, uint32_t c) { uint32_t r; asm("fma.rn.bf16x2 %0, %1, %2, %3;" : "=r"(r) : "r"(a), "r"(b), "r"(c)); return r; }
__device__ __forceinline__ float bf_lo(uint32_t w) { return __uint_as_float(w << 16); }
__device__ __forceinline__ float bf_hi(uint32_t w) { return __uint_as_float(w & 0xffff0000u); }
__device__ __forceinline__ int4 ldg_stream(const void* p, uint64_t pol) {
    int4 v;
    asm volatile("ld.global.nc.L1::no_allocate.L2::cache_hint.v4.s32 {%0,%1,%2,%3}, [%4], %5;"
                 : "=r"(v.x), "=r"(v.y), "=r"(v.z), "=r"(v.w) : "l"(p), "l"(pol));
    return v;
}
__device__ __forceinline__ uint4 lds_v4(uint32_t a) {
    uint4 v;
    asm volatile("ld.shared.v4.u32 {%0,%1,%2,%3}, [%4];" : "=r"(v.x), "=r"(v.y), "=r"(v.z), "=r"(v.w) : "r"(a) : "memory");
    return v;
}
__device__ __forceinline__ uint32_t lds_u32(uint32_t a) { uint32_t v; asm volatile("ld.shared.u32 %0, [%1];" : "=r"(v) : "r"(a) : "memory"); return v; }
template <int R> __device__ __forceinline__ void fence_regs(float (&d)[R]) {
#pragma unroll
    for (int i = 0; i < R; i++) asm volatile("" : "+f"(d[i])::"memory");
}
template <int R> __device__ __forceinline__ void fence_regs(uint32_t (&d)[R]) {
#pragma unroll
    for (int i = 0; i < R; i++) asm volatile("" : "+r"(d[i])::"memory");
}
template <bool B> struct Flag { static constexpr bool value = B; };

__device__ __forceinline__ void wgmma_ss_n128(float (&d)[64], uint32_t alo, uint32_t blo, int scale_d) {
    asm volatile(
        "{\n.reg .pred p;\n.reg .b64 da, db;\nsetp.ne.b32 p, %66, 0;\nmov.b64 da, {%64, 0x400000C0};\nmov.b64 db, {%65, 0x40000040};\n"
        "wgmma.mma_async.sync.aligned.m64n128k16.f32.bf16.bf16 "
        "{%0, %1, %2, %3, %4, %5, %6, %7, %8, %9, %10, %11, %12, %13, %14, %15, "
        "%16, %17, %18, %19, %20, %21, %22, %23, %24, %25, %26, %27, %28, %29, %30, %31, "
        "%32, %33, %34, %35, %36, %37, %38, %39, %40, %41, %42, %43, %44, %45, %46, %47, "
        "%48, %49, %50, %51, %52, %53, %54, %55, %56, %57, %58, %59, %60, %61, %62, %63}, "
        "da, db, p, 1, 1, 0, 0;\n}\n"
        :
          "+f"(d[0]), "+f"(d[1]), "+f"(d[2]), "+f"(d[3]), "+f"(d[4]), "+f"(d[5]), "+f"(d[6]), "+f"(d[7]),
          "+f"(d[8]), "+f"(d[9]), "+f"(d[10]), "+f"(d[11]), "+f"(d[12]), "+f"(d[13]), "+f"(d[14]), "+f"(d[15]),
          "+f"(d[16]), "+f"(d[17]), "+f"(d[18]), "+f"(d[19]), "+f"(d[20]), "+f"(d[21]), "+f"(d[22]), "+f"(d[23]),
          "+f"(d[24]), "+f"(d[25]), "+f"(d[26]), "+f"(d[27]), "+f"(d[28]), "+f"(d[29]), "+f"(d[30]), "+f"(d[31]),
          "+f"(d[32]), "+f"(d[33]), "+f"(d[34]), "+f"(d[35]), "+f"(d[36]), "+f"(d[37]), "+f"(d[38]), "+f"(d[39]),
          "+f"(d[40]), "+f"(d[41]), "+f"(d[42]), "+f"(d[43]), "+f"(d[44]), "+f"(d[45]), "+f"(d[46]), "+f"(d[47]),
          "+f"(d[48]), "+f"(d[49]), "+f"(d[50]), "+f"(d[51]), "+f"(d[52]), "+f"(d[53]), "+f"(d[54]), "+f"(d[55]),
          "+f"(d[56]), "+f"(d[57]), "+f"(d[58]), "+f"(d[59]), "+f"(d[60]), "+f"(d[61]), "+f"(d[62]), "+f"(d[63])
        : "r"(alo), "r"(blo), "r"(scale_d));
}

__device__ __forceinline__ void wgmma_rs_n192_tb(float (&d)[96], uint32_t a0, uint32_t a1, uint32_t a2, uint32_t a3, uint32_t blo, int scale_d) {
    asm volatile(
        "{\n.reg .pred p;\n.reg .b64 db;\nsetp.ne.b32 p, %101, 0;\nmov.b64 db, {%100, 0x40000040};\n"
        "wgmma.mma_async.sync.aligned.m64n192k16.f32.bf16.bf16 "
        "{%0, %1, %2, %3, %4, %5, %6, %7, %8, %9, %10, %11, %12, %13, %14, %15, "
        "%16, %17, %18, %19, %20, %21, %22, %23, %24, %25, %26, %27, %28, %29, %30, %31, "
        "%32, %33, %34, %35, %36, %37, %38, %39, %40, %41, %42, %43, %44, %45, %46, %47, "
        "%48, %49, %50, %51, %52, %53, %54, %55, %56, %57, %58, %59, %60, %61, %62, %63, "
        "%64, %65, %66, %67, %68, %69, %70, %71, %72, %73, %74, %75, %76, %77, %78, %79, "
        "%80, %81, %82, %83, %84, %85, %86, %87, %88, %89, %90, %91, %92, %93, %94, %95}, "
        "{%96, %97, %98, %99}, db, p, 1, 1, 1;\n}\n"
        :
          "+f"(d[0]), "+f"(d[1]), "+f"(d[2]), "+f"(d[3]), "+f"(d[4]), "+f"(d[5]), "+f"(d[6]), "+f"(d[7]),
          "+f"(d[8]), "+f"(d[9]), "+f"(d[10]), "+f"(d[11]), "+f"(d[12]), "+f"(d[13]), "+f"(d[14]), "+f"(d[15]),
          "+f"(d[16]), "+f"(d[17]), "+f"(d[18]), "+f"(d[19]), "+f"(d[20]), "+f"(d[21]), "+f"(d[22]), "+f"(d[23]),
          "+f"(d[24]), "+f"(d[25]), "+f"(d[26]), "+f"(d[27]), "+f"(d[28]), "+f"(d[29]), "+f"(d[30]), "+f"(d[31]),
          "+f"(d[32]), "+f"(d[33]), "+f"(d[34]), "+f"(d[35]), "+f"(d[36]), "+f"(d[37]), "+f"(d[38]), "+f"(d[39]),
          "+f"(d[40]), "+f"(d[41]), "+f"(d[42]), "+f"(d[43]), "+f"(d[44]), "+f"(d[45]), "+f"(d[46]), "+f"(d[47]),
          "+f"(d[48]), "+f"(d[49]), "+f"(d[50]), "+f"(d[51]), "+f"(d[52]), "+f"(d[53]), "+f"(d[54]), "+f"(d[55]),
          "+f"(d[56]), "+f"(d[57]), "+f"(d[58]), "+f"(d[59]), "+f"(d[60]), "+f"(d[61]), "+f"(d[62]), "+f"(d[63]),
          "+f"(d[64]), "+f"(d[65]), "+f"(d[66]), "+f"(d[67]), "+f"(d[68]), "+f"(d[69]), "+f"(d[70]), "+f"(d[71]),
          "+f"(d[72]), "+f"(d[73]), "+f"(d[74]), "+f"(d[75]), "+f"(d[76]), "+f"(d[77]), "+f"(d[78]), "+f"(d[79]),
          "+f"(d[80]), "+f"(d[81]), "+f"(d[82]), "+f"(d[83]), "+f"(d[84]), "+f"(d[85]), "+f"(d[86]), "+f"(d[87]),
          "+f"(d[88]), "+f"(d[89]), "+f"(d[90]), "+f"(d[91]), "+f"(d[92]), "+f"(d[93]), "+f"(d[94]), "+f"(d[95])
        : "r"(a0), "r"(a1), "r"(a2), "r"(a3), "r"(blo), "r"(scale_d));
}

struct Params {
    const int* qk; const int* qv;
    const __nv_bfloat16* ks; const __nv_bfloat16* kz; const __nv_bfloat16* vs; const __nv_bfloat16* vz;
    const __nv_bfloat16* q; __nv_bfloat16* out;
    uint8_t* pages;
    uint8_t* part;
    uint32_t zero;
};

constexpr float SCALE = 0.07216878364870322f * 1.4426950408889634f;
constexpr uint32_t VSCALE2 = 0x3f80u | ((uint32_t)(127 + VEXP) << 23);
__device__ __forceinline__ void set_flag(uint32_t flag) { asm volatile("st.shared.u8 [%0], %1;" ::"r"(flag), "r"(2) : "memory"); }
constexpr float QNORM2 = 14.f;
__device__ __forceinline__ void sq_acc(uint32_t (&x)[4], uint4 v) {
    x[0] = bf2_fma(v.x, v.x, x[0]); x[1] = bf2_fma(v.y, v.y, x[1]); x[2] = bf2_fma(v.z, v.z, x[2]); x[3] = bf2_fma(v.w, v.w, x[3]);
}
__device__ __forceinline__ float sq_sum(const uint32_t (&x)[4]) {
    const uint32_t y = bf2_add(bf2_add(x[0], x[1]), bf2_add(x[2], x[3]));
    return bf_lo(y) + bf_hi(y);
}
__device__ __forceinline__ bool q8_big(uint32_t rows) {
    uint32_t lane;
    asm volatile("mov.u32 %0, %laneid;" : "=r"(lane));
    uint32_t x[4] = {0, 0, 0, 0}, y[4] = {0, 0, 0, 0};
#pragma unroll
    for (int a = 0; a < 3; a++) { sq_acc(x, lds_v4(rows + lane * 16 + a * 1024)); sq_acc(y, lds_v4(rows + lane * 16 + a * 1024 + 512)); }
    float f = sq_sum(x), g = sq_sum(y);
#pragma unroll
    for (int m = 1; m < 8; m *= 2) { f += __shfl_xor_sync(0xffffffffu, f, m); g += __shfl_xor_sync(0xffffffffu, g, m); }
    return !(f <= QNORM2 && g <= QNORM2);
}

struct KScale {
    float s0, s1, s2, s3, n0, n1, n2, n3;
    __device__ __forceinline__ KScale(uint2 sc, uint2 z, float c) {
        s0 = bf_lo(sc.x) * SCALE; s1 = bf_hi(sc.x) * SCALE; s2 = bf_lo(sc.y) * SCALE; s3 = bf_hi(sc.y) * SCALE;
        n0 = fmaf(-bf_lo(z.x), s0, c); n1 = fmaf(-bf_hi(z.x), s1, c); n2 = fmaf(-bf_lo(z.y), s2, c); n3 = fmaf(-bf_hi(z.y), s3, c);
    }
    __device__ __forceinline__ uint2 operator()(int4 v) const {
        return make_uint2(pack_bf16(fmaf((float)v.x, s0, n0), fmaf((float)v.y, s1, n1)),
                          pack_bf16(fmaf((float)v.z, s2, n2), fmaf((float)v.w, s3, n3)));
    }
};
template <bool CHECK>
__device__ __forceinline__ uint32_t deq_v4(int4 v, uint32_t zs, uint32_t off, uint8_t* d0, uint8_t* d1) {
    const uint32_t z = __byte_perm(zs, 0, 0x1010), sc = __byte_perm(zs, 0, 0x3232);
    const uint32_t a = bf2_sub(pack_bf16((float)v.x, (float)v.y), z), b = bf2_sub(pack_bf16((float)v.z, (float)v.w), z);
    *(uint32_t*)d0 = bf2_fma(a, sc, off);
    *(uint32_t*)d1 = bf2_fma(b, sc, off);
    uint32_t far = 0;
    if (CHECK)
        asm("{\n.reg .b32 x, t;\nmax.xorsign.abs.bf16x2 x, %1, %2;\nmul.rn.bf16x2 x, x, %3;\nabs.bf16x2 x, x;\n"
            "mul.rn.bf16x2 t, %4, %5;\nset.ge.u32.bf16x2 %0, x, t;\n}\n" : "=r"(far) : "r"(a), "r"(b), "r"(sc), "r"(off), "r"(0x3e803e80u));
    return far;
}
__device__ __forceinline__ bool v_token_ok(uint32_t zs, uint32_t off) { return (off == 0) | (fabsf(bf_lo(zs) * bf_hi(zs)) <= 4.f * bf_lo(off)); }
__device__ __forceinline__ uint32_t v_offset(const Params& P, int head, int lane) {
    float w = __bfloat162float(__ldg(P.vs + (size_t)head * SEQ + lane)) * __bfloat162float(__ldg(P.vz + (size_t)head * SEQ + lane));
#pragma unroll
    for (int m = 16; m >= 1; m >>= 1) w += __shfl_xor_sync(0xffffffffu, w, m);
    w = fmaxf(w * (VOFF / 32.f * __uint_as_float((127 + VEXP) << 23)), 0.f);
    const uint32_t u = (__float_as_uint(w) + 0x00080000u) & 0xfff00000u;
    return u | u >> 16;
}
__device__ __forceinline__ void put_v_offset(uint32_t entry, uint32_t off) {
    asm volatile("st.shared.v2.b32 [%0 + 8], {%1, %2};" ::"r"(entry), "r"(off), "r"(__float_as_uint(-bf_lo(off) * __uint_as_float((127 - VEXP) << 23))) : "memory");
}
__device__ __forceinline__ void set_vbad(uint32_t flag) { asm volatile("st.shared.u8 [%0], %1;" ::"r"(flag), "r"(4) : "memory"); }
__device__ __forceinline__ uint32_t load_vzs(const Params& P, size_t idx) {
    return bf2_mul((uint32_t)__bfloat16_as_ushort(__ldg(P.vz + idx)) | ((uint32_t)__bfloat16_as_ushort(__ldg(P.vs + idx)) << 16), VSCALE2);
}
__device__ __forceinline__ void part_k(const Params& P, const uint8_t* src, const uint8_t* sp, const uint8_t* zp, uint8_t* slot, uint32_t doff, uint64_t pol,
                                       uint32_t koff) {
    int4 v[4];
    uint2 sc = __ldg((const uint2*)sp);
    const uint2 z = __ldg((const uint2*)zp);
#pragma unroll
    for (int a = 0; a < 4; a++) v[a] = ldg_stream(src + (a & 1) * 1536 + (a >> 1) * 6144, pol);
    uint32_t lo[4], hi[4];
    const float c = __uint_as_float(lds_u32(koff));
    {
        sc.x ^= v[3].w & P.zero;
        const float s0 = bf_lo(sc.x) * SCALE, s1 = bf_hi(sc.x) * SCALE, n0 = fmaf(-bf_lo(z.x), s0, c), n1 = fmaf(-bf_hi(z.x), s1, c);
#pragma unroll
        for (int a = 0; a < 4; a++) lo[a] = pack_bf16(fmaf((float)v[a].x, s0, n0), fmaf((float)v[a].y, s1, n1));
    }
    {
        sc.y ^= lo[3] & P.zero;
        const float s0 = bf_lo(sc.y) * SCALE, s1 = bf_hi(sc.y) * SCALE, n0 = fmaf(-bf_lo(z.y), s0, c), n1 = fmaf(-bf_hi(z.y), s1, c);
#pragma unroll
        for (int a = 0; a < 4; a++) hi[a] = pack_bf16(fmaf((float)v[a].z, s0, n0), fmaf((float)v[a].w, s1, n1));
    }
    doff ^= lo[3] & P.zero;
#pragma unroll
    for (int a = 0; a < 4; a++) *(uint2*)(slot + ((a & 1) ? (doff ^ 32) + 256 : doff) + (a >> 1) * 1024) = make_uint2(lo[a], hi[a]);
}
template <bool CHECK>
__device__ __forceinline__ bool part_v(const Params& P, const uint8_t* src, size_t key0, int h, uint8_t* slot, uint32_t doff, uint64_t pol, uint32_t voff) {
    int4 v[4];
#pragma unroll
    for (int a = 0; a < 4; a++) v[a] = ldg_stream(src + (a & 1) * 1536 + (a >> 1) * 6144, pol);
    uint32_t ln;
    asm volatile("mov.u32 %0, %laneid;" : "=r"(ln));
    const uint32_t zs = load_vzs(P, key0 + (ln & 15));
    int r0 = 4 * h + (ln >> 4);
    r0 ^= v[3].w & P.zero;
    doff ^= v[3].w & P.zero;
    uint8_t* d0 = slot + doff; uint8_t* d1 = slot + (doff ^ 32);
    const uint32_t off = lds_u32(voff);
    uint32_t m = 0;
#pragma unroll
    for (int a = 0; a < 4; a++) {
        const int o = (a & 1) * 256 + (a >> 1) * 1024;
        m |= deq_v4<CHECK>(v[a], __shfl_sync(0xffffffffu, zs, r0 + (a & 1) * 2 + (a >> 1) * 8), off, ((a & 1) ? d1 : d0) + o, ((a & 1) ? d0 : d1) + o) & (0x00010001u << a);
    }
    if (!CHECK) return true;
    m = ((m | m >> 16) & 15) << (r0 & 1) * 4;
    if (!v_token_ok(zs, off)) m |= 256;
    return __reduce_or_sync(0xffffffffu, m) == 255;
}
template <int N = 1, int STEP = 0>
__device__ __forceinline__ void start_k(const Params& P, int head, int key0, uint8_t* img, int w, int lane, uint64_t pol, float koff) {
    const int hw = lane >> 4, l16 = lane & 15;
    const uint8_t* src = (const uint8_t*)(P.qk + ((size_t)head * SEQ + key0) * DH) + (uint32_t)(w * 3072 + hw * 768 + l16 * 16);
    int4 v[N][3][2]; uint2 z[N][3], sc[N][3];
#pragma unroll
    for (int n = 0; n < N; n++) {
        const size_t so = ((size_t)head * 32 + (key0 + n * STEP >> 6)) * DH + l16 * 4;
#pragma unroll
        for (int c = 0; c < 3; c++) {
            v[n][c][0] = ldg_stream(src + n * STEP * DH * 4 + c * 256, pol); v[n][c][1] = ldg_stream(src + n * STEP * DH * 4 + 1536 + c * 256, pol);
            z[n][c] = __ldg((const uint2*)(P.kz + so + c * 64)); sc[n][c] = __ldg((const uint2*)(P.ks + so + c * 64));
        }
    }
    if (N > 1) img += v[N - 1][2][1].w & P.zero;
#pragma unroll
    for (int n = 0; n < N; n++)
#pragma unroll
        for (int c = 0; c < 3; c++) {
            const KScale f(sc[n][c], z[n][c], koff);
#pragma unroll
            for (int a = 0; a < 2; a++) {
                const int row = (key0 + n * STEP & 127) + 4 * w + 2 * a + hw;
                *(uint2*)(img + c * SUB + row * 128 + (((l16 >> 1) ^ (row & 7)) << 4) + (l16 & 1) * 8) = f(v[n][c][a]);
            }
        }
}
template <int OFFSET, int N = 1, int STEP = 0>
__device__ __forceinline__ bool start_v(const Params& P, int head, int key0, uint8_t* img, int w, int lane, uint64_t pol, uint32_t off = 0) {
    const int hw = lane >> 4, l16 = lane & 15, g = (l16 >> 3) * 4 + (l16 & 1);
    const uint8_t* src = (const uint8_t*)(P.qv + ((size_t)head * SEQ + key0) * DH) + (uint32_t)(w * 1536 + hw * 768 + l16 * 16);
    int4 v[N][3];
    uint32_t zs[N];
#pragma unroll
    for (int n = 0; n < N; n++)
#pragma unroll
        for (int c = 0; c < 3; c++) v[n][c] = ldg_stream(src + n * STEP * DH * 4 + c * 256, pol);
#pragma unroll
    for (int n = 0; n < N; n++) zs[n] = load_vzs(P, (size_t)head * SEQ + key0 + n * STEP + 2 * w + hw);
    if (OFFSET == 1) off = v_offset(P, head, lane);
    if (N > 1) img += v[N - 1][2].w & P.zero;
    bool ok = true;
#pragma unroll
    for (int n = 0; n < N; n++) {
        const int row = (key0 + n * STEP & 127) + 2 * w + hw;
        uint32_t far = 0;
#pragma unroll
        for (int c = 0; c < 3; c++) {
            uint8_t* d = img + c * SUB + row * 128 + ((l16 >> 1) & 3) * 4;
            far |= deq_v4<OFFSET != 0>(v[n][c], zs[n], off, d + ((g ^ (row & 7)) << 4), d + ((g ^ 2 ^ (row & 7)) << 4));
        }
        if (OFFSET) {
            const uint32_t b = __ballot_sync(0xffffffffu, far != 0);
            ok &= (b & 0xffff) && (b >> 16) && __all_sync(0xffffffffu, v_token_ok(zs[n], off));
        }
    }
    return ok;
}

__device__ __forceinline__ void proxy_fence_global() { asm volatile("fence.proxy.async.global;" ::: "memory"); }
__device__ __forceinline__ void publish(unsigned long long* flag, int byte, uint32_t val) {
    proxy_fence_global();
    asm volatile("st.release.gpu.global.u8 [%0], %1;" ::"l"((uint8_t*)flag + byte), "r"(val) : "memory");
}
__device__ __forceinline__ void wait_flag(const unsigned long long* f, uint32_t redo) {
    uint32_t n = 0;
    while (true) {
        unsigned long long v;
        asm volatile("ld.acquire.gpu.global.u64 %0, [%1];" : "=l"(v) : "l"(f) : "memory");
        if (__all_sync(0xffffffffu, (v & TILE_READY) == TILE_READY)) {
            if (redo && (((uint32_t)v | (uint32_t)(v >> 32)) & FLAG_VBAD)) set_flag(redo);
            __syncwarp();
            break;
        }
        if (++n > SPIN_LIMIT) __trap();
        __nanosleep(20);
    }
}
__device__ __forceinline__ void wait_flags(const unsigned long long* f, uint32_t skip, uint32_t koff, uint32_t redo) {
    constexpr uint32_t READY = (uint32_t)TILE_READY;
    uint32_t n = 0;
    while (true) {
        uint32_t a, b, c, d;
        asm volatile("ld.acquire.gpu.global.v4.u32 {%0, %1, %2, %3}, [%4];" : "=r"(a), "=r"(b), "=r"(c), "=r"(d) : "l"(f) : "memory");
        if (__all_sync(0xffffffffu, (a & b & ((c & d) | skip) & READY) == READY)) {
            if ((a | b | c | d) != READY) {
                if (koff) asm volatile("st.shared.v4.u32 [%0], {%1, %1, %1, %1};" ::"r"(koff), "r"(0) : "memory");
                if ((c | d) & ~skip & FLAG_VBAD) set_flag(redo);
            }
            __syncwarp();
            break;
        }
        if (++n > SPIN_LIMIT) __trap();
        __nanosleep(20);
    }
}
__device__ __forceinline__ uint32_t atom_add0(const void* p, uint32_t x) {
    uint32_t v;
    asm volatile("{\n.reg .pred p;\n.reg .u32 l;\nmov.u32 l, %laneid;\nsetp.eq.u32 p, l, 0;\nmov.u32 %0, 0;\n"
                 "@p atom.relaxed.gpu.global.add.u32 %0, [%1], %2;\n}\n" : "=r"(v) : "l"(p), "r"(x) : "memory");
    return v;
}
__device__ __forceinline__ uint32_t clock_after(uint32_t v) {
    uint32_t c;
    asm volatile("{\n.reg .u32 t;\nshfl.sync.idx.b32 t, %1, 0, 31, 0xffffffff;\nmov.u32 %0, %clock;\nadd.u32 %0, %0, t;\n}\n" : "=r"(c) : "r"(v) : "memory");
    return c;
}
__device__ __forceinline__ void wait_until(uint32_t c0, uint32_t clks) {
    while (__shfl_sync(0xffffffffu, (uint32_t)clock() - c0, 0) < clks) __nanosleep(32);
}
__device__ __forceinline__ void cluster_arrive() { asm volatile("barrier.cluster.arrive.relaxed.aligned;" ::: "memory"); }
__device__ __forceinline__ void cluster_wait() { asm volatile("barrier.cluster.wait.acquire.aligned;" ::: "memory"); }

struct Softmax {
    float m0, m1, l0, l1, a0, a1;
    bool fast, resc;

    template <bool first> __device__ __forceinline__ void run(float (&s)[64]) {
        if (first) { l0 = 0.f; l1 = 0.f; }
        if (fast) {
            resc = false;
#pragma unroll
            for (int j = 0; j < 64; j++) s[j] = ex2(s[j]);
            float x0 = s[0], x1 = s[2], y0 = s[1], y1 = s[3];
#pragma unroll
            for (int j = 1; j < 16; j++) { x0 += s[4 * j]; y0 += s[4 * j + 1]; x1 += s[4 * j + 2]; y1 += s[4 * j + 3]; }
            l0 += x0 + y0; l1 += x1 + y1;
        } else {
            float x0 = fmaxf(s[0], s[1]), x1 = fmaxf(s[2], s[3]), y0 = fmaxf(s[4], s[5]), y1 = fmaxf(s[6], s[7]);
#pragma unroll
            for (int j = 2; j < 16; j += 2) {
                x0 = fmaxf(x0, fmaxf(s[4 * j], s[4 * j + 1]));     x1 = fmaxf(x1, fmaxf(s[4 * j + 2], s[4 * j + 3]));
                y0 = fmaxf(y0, fmaxf(s[4 * j + 4], s[4 * j + 5])); y1 = fmaxf(y1, fmaxf(s[4 * j + 6], s[4 * j + 7]));
            }
            x0 = fmaxf(x0, y0); x1 = fmaxf(x1, y1);
            x0 = fmaxf(x0, __shfl_xor_sync(0xffffffffu, x0, 1));
            x1 = fmaxf(x1, __shfl_xor_sync(0xffffffffu, x1, 1));
            x0 = fmaxf(x0, __shfl_xor_sync(0xffffffffu, x0, 2));
            x1 = fmaxf(x1, __shfl_xor_sync(0xffffffffu, x1, 2));
            if (first) {
                a0 = 0.f; a1 = 0.f;
                resc = false;
            } else {
                x0 = fmaxf(x0, m0); x1 = fmaxf(x1, m1);
                a0 = ex2(m0 - x0); a1 = ex2(m1 - x1);
                resc = __any_sync(0xffffffffu, x0 != m0 || x1 != m1);
            }
            m0 = x0; m1 = x1;
            float r0 = 0.f, r1 = 0.f;
#pragma unroll
            for (int j = 0; j < 16; j++) {
                s[4 * j] = ex2(s[4 * j] - x0); s[4 * j + 1] = ex2(s[4 * j + 1] - x0);
                s[4 * j + 2] = ex2(s[4 * j + 2] - x1); s[4 * j + 3] = ex2(s[4 * j + 3] - x1);
                r0 += s[4 * j] + s[4 * j + 1];
                r1 += s[4 * j + 2] + s[4 * j + 3];
            }
            l0 = fmaf(l0, a0, r0); l1 = fmaf(l1, a1, r1);
        }
    }
    __device__ __forceinline__ void pack(const float (&s)[64], uint32_t (&p)[32]) {
#pragma unroll
        for (int j = 0; j < 32; j++) p[j] = pack_bf16(s[2 * j], s[2 * j + 1]);
    }
    __device__ __forceinline__ void rescale(float (&o)[96]) {
        if (resc) {
#pragma unroll
            for (int i = 0; i < 24; i++) { o[4 * i] *= a0; o[4 * i + 1] *= a0; o[4 * i + 2] *= a1; o[4 * i + 3] *= a1; }
        }
    }
    __device__ __forceinline__ void sums(float& f0, float& f1, uint32_t redo) {
        f0 = l0 + __shfl_xor_sync(0xffffffffu, l0, 1); f1 = l1 + __shfl_xor_sync(0xffffffffu, l1, 1);
        f0 += __shfl_xor_sync(0xffffffffu, f0, 2); f1 += __shfl_xor_sync(0xffffffffu, f1, 2);
        constexpr uint32_t lo = (127 - 40) << 23, span = 80 << 23;
        if (__any_sync(0xffffffffu, __float_as_uint(f0) - lo > span || __float_as_uint(f1) - lo > span)) { fast = false; set_flag(redo); }
    }
    __device__ __forceinline__ void finish(float& i0, float& i1, uint32_t redo) {
        float f0, f1;
        sums(f0, f1, redo);
        i0 = rcp(f0 * __uint_as_float((127 + VEXP) << 23)); i1 = rcp(f1 * __uint_as_float((127 + VEXP) << 23));
    }
};
__device__ __forceinline__ void q_first(const CUtensorMap* qmap, uint32_t dst, int row0, uint32_t bar) {
#pragma unroll
    for (int w = 0; w < 4; w++) { mbar_expect_tx(bar, 6144); tma_load_q16(dst + w * 6144, qmap, (row0 >> 3) + 2 * w, bar); }
}

__device__ __forceinline__ uint4 out_word(const float (&o)[96], int k, float i0, float i1, float c0, float c1) {
    const int b = 16 * (k >> 1) + 2 * (k & 1);
    const float i = (k & 1) ? i1 : i0, c = (k & 1) ? c1 : c0;
    return make_uint4(pack_bf16(fmaf(o[b], i, c), fmaf(o[b + 1], i, c)), pack_bf16(fmaf(o[b + 8], i, c), fmaf(o[b + 9], i, c)),
                      pack_bf16(fmaf(o[b + 4], i, c), fmaf(o[b + 5], i, c)), pack_bf16(fmaf(o[b + 12], i, c), fmaf(o[b + 13], i, c)));
}

__device__ __forceinline__ void helper_cta(const Params& P, const CUtensorMap& qmap, uint32_t sb, uint32_t clk0, int w8) {
    int tid, h;
    uint8_t* img;
    asm volatile("mov.u32 %0, %tid.x;" : "=r"(tid));
    asm volatile("mov.u32 %0, %ctaid.x;" : "=r"(h));
    asm volatile("{\n.reg .u64 a;\ncvt.u64.u32 a, %1;\ncvta.shared.u64 %0, a;\n}\n" : "=l"(img) : "r"(sb));
    h = __shfl_sync(0xffffffffu, h - NCTA, 0);
    const int cw = w8 >> 2, lane = tid & 31;
    const uint64_t pol = policy_evict_first();
    const uint32_t sl = sb & 0x3FFFF;
    const uint32_t kdesc = ((sl + SM_K) >> 4) | (1u << 16), vdesc = ((sl + SM_V) >> 4) | ((SUB >> 4) << 16);
    auto load_q = [&](int n, int g) {
        asm volatile("{\n.reg .pred p;\nelect.sync _|p, 0xffffffff;\n"
                     "@p mbarrier.arrive.expect_tx.shared::cta.b64 _, [%2], 6144;\n"
                     "@p cp.async.bulk.tensor.4d.shared::cluster.global.mbarrier::complete_tx::bytes [%0], [%1, {%3, %3, %3, %4}], [%2];\n}\n"
                     ::"r"(sb + (n & 1 ? SM_V + TILE : SM_Q) + w8 * 6144), "l"(&qmap), "r"(sb + B_HQ + (n & 1) * 16 + 8 * cw), "r"(0),
                       "r"((3 * NCTA + g * 16 + (n & 15)) * 16 + w8 * 2) : "memory");
    };
    auto codes_to_l2 = [&](int g) {
        const size_t off = ((size_t)(3 * NGROUP + g) * SEQ + 15 * 128 + w8 * 16) * DH;
        l2_prefetch(P.qk + off, 12288); l2_prefetch(P.qv + off, 12288);
        const size_t hd = 3 * NGROUP + g;
        if (w8 < 6) l2_prefetch((const uint8_t*)(&P.ks)[(w8 & 1) + (w8 & 6 ? 2 : 0)] + (w8 & 6 ? hd * SEQ * 2 + (w8 & 4 ? 0 : 15 * 256) : (hd * 32 + 30) * DH * 2), w8 & 6 ? 256 : 768);
    };
    float o[96], s[64];
    uint32_t p[32];
    Softmax sm;
    sm.fast = true; sm.resc = false; sm.m0 = 0.f; sm.m1 = 0.f; sm.a0 = 0.f; sm.a1 = 0.f;
    wait_until(clk0, HELP_T0 - 3000);
    codes_to_l2(2 * h);
    wait_until(clk0, HELP_T0);
#pragma unroll 1
    for (int g = 2 * h; g < 2 * h + 2; g++) {
        const int head = 3 * NGROUP + g, n0 = (g & 1) * 16;
        load_q(n0, g); load_q(n0 + 1, g);
        bool good = true;
        const int ln = lane;
#pragma unroll 1
        for (int a = 0; a < 4; a += 2) start_k<2, 32>(P, head, 15 * 128 + cw * 16 + a * 32, img + SM_K, w8 & 3, ln, pol, KOFF);
        const uint32_t off = v_offset(P, head, ln);
#pragma unroll 1
        for (int a = 0; a < 8; a += 8) good &= start_v<2, 8, 16>(P, head, 15 * 128 + a * 16, img + SM_V, w8, ln, pol, off);
        const float c = -bf_lo(off) * __uint_as_float((127 - VEXP) << 23);
        if (!good) set_flag(sb + SM_REDO);
        asm volatile("fence.proxy.async.shared::cta;" ::: "memory");
        bar_sync(3);
        auto qk = [&](int n) {
            const uint32_t z = (n + g) & P.zero;
            const uint32_t qdesc = (((sl + (n & 1 ? SM_V + TILE : SM_Q) + cw * 24576) >> 4) | (1u << 16)) + z, kd = kdesc + z;
#pragma unroll
            for (int k = 0; k < 12; k++) wgmma_ss_n128(s, qdesc + (k >> 2) * 64 + (k & 3) * 2, kd + (k >> 2) * (SUB >> 4) + (k & 3) * 2, k != 0);
            wg_commit();
        };
        auto wait_q = [&](int n) { mbar_wait(sb + B_HQ + (n & 1) * 16 + 8 * cw, (n >> 1) & 1); };
#pragma unroll
        for (int i = 0; i < 96; i++) asm volatile("" : "=f"(o[i]));
#pragma unroll
        for (int i = 0; i < 64; i++) asm volatile("" : "=f"(s[i]));
        if (cw == 0) bar_arrive(1);
        wait_q(n0);
        bar_sync(1 + cw);
        wg_fence();
        qk(n0);
        bar_arrive(1 + (cw ^ 1));
        wg_wait<0>();
        fence_regs(s);
        load_q(n0 + 2, g);
        sm.run<true>(s);
        sm.pack(s, p);
        auto job = [&](int n, auto MORE) {
            constexpr bool more = decltype(MORE)::value;
            float f0, f1;
            sm.sums(f0, f1, sb + SM_REDO);
            sm.fast = true;
            const float i0 = rcp(f0 * __uint_as_float((127 + VEXP) << 23)), i1 = rcp(f1 * __uint_as_float((127 + VEXP) << 23));
            uint8_t* d = P.part + (size_t)((g * 16 + (n & 15)) * 2 + cw) * PART_WG + (tid & 127) * 16;
            *(float4*)(d + 12 * 2048) = make_float4(f0, f1, 0.f, 0.f);
            if (more) wait_q(n + 1);
            bar_sync(1 + cw);
            fence_regs(o); fence_regs(p);
            wg_fence();
            if (more) qk(n + 1);
#pragma unroll
            for (int k = 0; k < 8; k++) wgmma_rs_n192_tb(o, p[4 * k], p[4 * k + 1], p[4 * k + 2], p[4 * k + 3], vdesc + (n & P.zero) + k * 128, k != 0);
            wg_commit();
            bar_arrive(1 + (cw ^ 1));
            if (more) {
                wg_wait<1>();
                fence_regs(s);
                if (n + 3 < n0 + 16) load_q(n + 3, g);
                sm.run<true>(s);
                fence_regs(s);
            }
            wg_wait<0>();
            fence_regs(o);
#pragma unroll
            for (int k = 0; k < 12; k++) *(uint4*)(d + k * 2048) = out_word(o, k, i0, i1, c, c);
            if (more) sm.pack(s, p);
        };
#pragma unroll 1
        for (int n = n0; n < n0 + 15; n++) {
            if (n == 8) codes_to_l2(g + 1);
            job(n, Flag<true>());
        }
        job(n0 + 15, Flag<false>());
        if (cw == 0) bar_sync(1);
        bar_sync(3);
        if (tid == 128) {
            const uint32_t v = 1 | (lds_u32(sb + SM_REDO) ? 4 : 0);
            asm volatile("st.shared.u32 [%0], %1;" ::"r"(sb + SM_REDO), "r"(0) : "memory");
            proxy_fence_global();
            asm volatile("st.release.gpu.global.u32 [%0], %1;" ::"l"(P.pages + ctl_off(g) + CTL_PART), "r"(v) : "memory");
        }
        bar_sync(3);
    }
}

template <bool HELP>
__global__ void __cluster_dims__(CLUSTER, 1, 1) __launch_bounds__(512, 1)
kvq_attn_kernel(const __grid_constant__ Params P, const __grid_constant__ CUtensorMap qmap) {
    constexpr int NT = TOTAL - HELP;
    extern __shared__ uint8_t smem_raw[];
    const uint32_t sb = (smem_u32(smem_raw) + 1023) & ~1023u;
    const int tid = threadIdx.x;
    if (HELP && blockIdx.x >= NCTA) {
        const uint32_t clk0 = (uint32_t)clock();
        if (tid == 0) {
            asm volatile("prefetch.tensormap [%0];" ::"l"(&qmap) : "memory");
            for (int i = 0; i < 4; i++) mbar_init(sb + B_HQ + 8 * i, 4);
            asm volatile("st.shared.u32 [%0], %1;" ::"r"(sb + SM_REDO), "r"(0) : "memory");
            asm volatile("fence.mbarrier_init.release.cluster;" ::: "memory");
            asm volatile("fence.proxy.async.shared::cta;" ::: "memory");
        }
        __syncthreads();
        const int hw = __shfl_sync(0xffffffffu, tid >> 5, 0);
        if ((hw >> 2) == 0 || (hw >> 2) == 3) { asm volatile("setmaxnreg.dec.sync.aligned.u32 32;"); return; }
        asm volatile("setmaxnreg.inc.sync.aligned.u32 224;");
        helper_cta(P, qmap, sb, clk0, hw - 4);
        return;
    }
    if (tid == 128) {
        const uint32_t b = blockIdx.x;
        const uint8_t* src = *(const uint8_t* const*)((const uint8_t*)&P.qk + (b & 8)) + ((b >> 4) * (SEQ / 16) + (b & 7)) * (16 * DH * 4);
        asm volatile("{\n.reg .pred p;\nsetp.eq.u32 p, %1, 0;\ncp.async.bulk.prefetch.L2.global [%0], 12288;\n"
                     "@p cp.async.bulk.prefetch.L2.global [%0 + 98304], 12288;\n}\n" ::"l"(src), "r"(b & 8) : "memory");
    }
    const int warp = __shfl_sync(0xffffffffu, tid >> 5, 0), wg = warp >> 2;
    const uint32_t clk0 = (uint32_t)clock();
    auto role = [&]() { mbar_wait_sleep(sb + B_ROLE, 0); return __shfl_sync(0xffffffffu, lds_u32(sb + SM_ROLE), 0); };

    if (tid == 160) { TS(0, 70); }
    if (wg == 0 || wg == 3) {
        const int lane = tid & 31;
        const uint32_t crank = blockIdx.x % CLUSTER;
        uint32_t* state = (uint32_t*)(P.pages + CTL_STATE);
        uint8_t* probe = P.pages + ctl_off(warp & 7) + CTL_PROBE + (blockIdx.x >> 1) * 32;
        uint32_t v0 = 0;
        if (crank == 0) {
            asm volatile("{\n.reg .pred p;\nsetp.lt.u32 p, %2, 2;\n@p st.global.v4.u32 [%0], {%1, %1, %1, %1};\n}\n"
                         ::"l"(probe + lane * 16), "r"(0), "r"(lane) : "memory");
            v0 = atom_add0(probe, 0);
        } else if (warp > 3) {
            const uint32_t n = warp & 2 ? 512 : 1536;
            l2_prefetch((const uint8_t*)(&P.ks)[warp & 3] + (blockIdx.x >> 1) * n, n);
        } else {
            asm volatile("{\n.reg .pred p;\nsetp.eq.u32 p, %4, 0;\n@p st.relaxed.gpu.global.v4.u32 [%0], {%1, %2, %3, %3};\n}\n"
                         ::"l"(state + (lane & 1) * 4), "r"(ST_OPEN), "r"(PAR_OPEN), "r"(0), "r"(((tid ^ 64) | blockIdx.x) >> 1) : "memory");
        }
        if (tid == 0) {
            asm volatile("prefetch.tensormap [%0];" ::"l"(&qmap) : "memory");
            for (int i = 0; i < KSLOTS; i++) { mbar_init(sb + B_KFULL + 8 * i, 1); mbar_init(sb + B_KEMPTY + 8 * i, 2 * CLUSTER); }
            for (int i = 0; i < 2; i++) {
                mbar_init(sb + B_VFULL + 8 * i, 1); mbar_init(sb + B_VEMPTY + 8 * i, 2 * CLUSTER);
                mbar_init(sb + B_QFULL + 8 * i, 4);
            }
            for (int i = 0; i < 8; i++) mbar_init(sb + B_UNIT + 8 * i, 6);
            mbar_init(sb + B_ROLE, 1); mbar_expect_tx(sb + B_ROLE, 4);
            if (HELP) { mbar_init(sb + B_PART, 1); mbar_init(sb + B_PART + 8, 1); mbar_init(sb + B_PFLAG, 1); }
            for (int i = 0; i < 4; i++) asm volatile("st.shared.v4.f32 [%0], {%1, %2, %2, %2};" ::"r"(sb + SM_OFF + 16 * i), "f"(KOFF), "f"(0.f) : "memory");
            asm volatile("st.shared.v4.u32 [%0], {%1, %2, %2, %2};" ::"r"(sb + SM_PROG), "r"(-64), "r"(0) : "memory");
            asm volatile("fence.acq_rel.cta;" ::: "memory");
            asm volatile("fence.mbarrier_init.release.cluster;" ::: "memory");
            asm volatile("fence.proxy.async.shared::cta;" ::: "memory");
        }
        __syncwarp();
        cluster_arrive();
        asm volatile("setmaxnreg.dec.sync.aligned.u32 32;");
        auto pf_scales = [&](int item, int id) {
            const size_t h = item * NGROUP + (id >> 4);
            const int r = id & 15;
            l2_prefetch(P.ks + h * 32 * DH + r * 384, 768); l2_prefetch(P.kz + h * 32 * DH + r * 384, 768);
            l2_prefetch(P.vs + h * SEQ + r * 128, 256);     l2_prefetch(P.vz + h * SEQ + r * 128, 256);
        };
        if (crank == 0) {
            asm volatile("bar.sync 5, %0;" ::"r"(256 + __shfl_sync(0xffffffffu, v0, 0)) : "memory");
            const uint32_t c0 = clock_after(v0);
            const uint32_t c1 = clock_after(atom_add0(probe, 0));
            asm volatile("st.shared.u32 [%0], %1;" ::"r"(sb + SM_LAT + (warp & 7) * 4), "r"(c1 - c0) : "memory");
            cluster_wait();
            if (warp != 1) bar_arrive(4);
            else {
                bar_sync(4);
                uint2 a;
                asm volatile("ld.shared.v2.u32 {%0,%1}, [%2];" : "=r"(a.x), "=r"(a.y) : "r"(sb + SM_LAT + (lane & 3) * 8) : "memory");
                uint32_t par = __ballot_sync(0xffffffffu, a.x > a.y) & 15, par0 = 0;
                const uint32_t side = par & 1;
                par = (par ^ (side * 15)) | 16;
                uint32_t n = 0;
#pragma unroll 1
                for (int i = 0; !(n & ST_OPEN) || !par0; i++) {
                    if (i >> 16) __trap();
                    asm volatile("{\n.reg .pred p, q;\nsetp.eq.u32 p, %5, 0;\nsetp.ge.and.s32 q, %0, 0, p;\n"
                                 "@p atom.relaxed.gpu.global.cas.b32 %1, [%2 + 4], %6, %4;\n"
                                 "@q atom.relaxed.gpu.global.add.u32 %0, [%2], %3;\n}\n"
                                 : "+r"(n), "+r"(par0) : "l"(state), "r"(side ? 256 : 1), "r"(par), "r"(lane), "n"(PAR_OPEN) : "memory");
                    n = __shfl_sync(0xffffffffu, n, 0); par0 = __shfl_sync(0xffffffffu, par0, 0);
                }
                if (par0 != PAR_OPEN) par = par0;
                n = side ? 63 - (n >> 8 & 255) : n & 255;
                const uint32_t up = n >> 5, k = up ? 63 - n : n;
                const uint32_t id = (((k >> 3) * 2 + ((par >> (k >> 3) & 1) ^ up)) * 8 + (k & 7)) * CLUSTER;
                asm volatile("{\n.reg .u32 a;\n.reg .pred p;\nsetp.lt.u32 p, %1, 2;\nmapa.shared::cluster.u32 a, %0, %3;\n"
                             "@p st.async.weak.shared::cluster.mbarrier::complete_tx::bytes.u32 [a + 8], %2, [a];\n}\n"
                             ::"r"(sb + B_ROLE), "r"(lane), "r"(id + lane), "r"(lane & 1) : "memory");
            }
        } else {
#pragma unroll 1
            for (int i = 0; i < (warp == 3 ? 12 : 0); i++) {
                wait_until(clk0, Q_T0 + i * Q_DT);
                l2_prefetch(P.q + (size_t)((blockIdx.x - (i & 1)) * 128 * DH + (i >> 1) * 4096), 8192);
            }
            cluster_wait();
        }
        const int bid = role(), grp = bid >> 4, rk = bid & 15;
        uint8_t* ring = P.pages + (grp >> 1) * PAGE;
        unsigned long long* flags = (unsigned long long*)(P.pages + ctl_off(grp));
        if (warp == 0) {
            wait_until(clk0, POLL_T);
            __syncwarp();
            constexpr int VSEP = 8;
            uint32_t kslot = 0, kphase = 1;
            auto load_k = [&](int t, int c) {
                if (t >= NT) return;
                if (c == 0) {
                    if (t > 1) { TP(5, t); }
                    if (t == 0) wait_flag(flags + CTL_PROBE / 8 + (grp * 8 + (lane & 3)) * 4, 0);
                    else if (t > 1) wait_flags(flags + 2 * t, t > VSEP ? 0 : ~0u, (t & 15) == 13 ? sb + SM_OFF + (t >> 4) * 16 + 16 : 0, sb + SM_REDO + (t - 1 >> 4));
                    TP(6, t);
                    const int prog = t + (int)(0x94000000u >> (t & 15) * 2 & 3);
                    if (lane == 0) asm volatile("red.release.cta.shared.max.s32 [%0], %1;" ::"r"(sb + SM_PROG), "r"(prog) : "memory");
                }
                mbar_wait_sleep(sb + B_KEMPTY + 8 * kslot, kphase);
                bulk_load_mc<1>(sb + SM_K + kslot * SUB + crank * 8192, ring + (ring_off(grp, t, crank) + c * SUB), sb + B_KFULL + 8 * kslot);
                if (++kslot == KSLOTS) { kslot = 0; kphase ^= 1; }
            };
            auto load_v = [&](int t) {
                if (t >= NT) return;
                if (t < 8) { TP(5, 64 + t); }
                if (t == 0) wait_flag(flags + CTL_PROBE / 8 + (grp * 8 + 4 + (lane & 3)) * 4, sb + SM_REDO);
                else if (t < VSEP || t == NT - 1) wait_flag(flags + 2 * t + 3, sb + SM_REDO + (t >> 4));
                if (t < 8) { TP(6, 64 + t); }
                const int s = t & 1;
                mbar_wait_sleep(sb + B_VEMPTY + 8 * s, ((t >> 1) & 1) ^ 1);
                bulk_load_mc<3>(sb + SM_V + s * TILE + crank * 8192, ring + ring_off(grp, t, 2 + crank), sb + B_VFULL + 8 * s);
            };
            load_k(0, 0); load_k(0, 1); load_k(0, 2);
            if (lane == 0) q_first(&qmap, sb + SM_Q + 24576, bid * 128 + 64, sb + B_QFULL + 8);
            __syncwarp();
            load_k(1, 0); load_k(1, 1); load_v(0);
#pragma unroll 1
            for (int i = -1; i < NT - 2; i++) {
                if ((i & 15) == 7 && i < TOTAL - 16) pf_scales((i >> 4) + 1, bid);
                if ((i & 15) >= QPF && (i & 15) < QPF + 4 && i < TOTAL - 16)
                    l2_prefetch(P.q + (size_t)(((i >> 4) + 1) * NCTA + bid) * 128 * DH + ((i & 15) - QPF) * 32 * DH, 12288);
                load_k(i + 2, 2); load_k(i + 3, 0); load_k(i + 3, 1);
                load_v(i + 2);
            }
            if (HELP) {
                mbar_wait_sleep(sb + B_PFLAG, 0);
#pragma unroll 1
                for (int j = 0; j < 4; j++) {
                    mbar_wait_sleep(sb + B_KEMPTY + 8 * kslot, kphase);
                    asm volatile("{\n.reg .pred p, q;\nelect.sync _|p, 0xffffffff;\nsetp.eq.and.u32 q, %5, 0, p;\n"
                                 "@q mbarrier.arrive.expect_tx.shared::cta.b64 _, [%2], %4;\n"
                                 "@p cp.async.bulk.shared::cluster.global.mbarrier::complete_tx::bytes [%0], [%1], %3, [%2];\n}\n"
                                 ::"r"(sb + SM_K + kslot * SUB), "l"(P.part + (size_t)(bid * 2 + (j >> 1)) * PART_WG + (j & 1) * SUB), "r"(sb + B_PART + (j >> 1) * 8),
                                   "r"(j & 1 ? PART_WG - SUB : SUB), "n"(PART_WG), "r"(j & 1) : "memory");
                    if (++kslot == KSLOTS) { kslot = 0; kphase ^= 1; }
                }
            }
            unsigned int old = 0;
            if (lane == 0) asm volatile("atom.acq_rel.gpu.global.add.u32 %0, [%1], 1;" : "=r"(old) : "l"(state + 8) : "memory");
            if (__shfl_sync(0xffffffffu, old, 0) == NCTA - 1) {
                __syncwarp();
#pragma unroll 1
                for (int g = 0; g < NGROUP; g++) {
                    uint4* c = (uint4*)(P.pages + ctl_off(g));
                    c[1 + lane] = c[33 + lane] = c[CTL_PROBE / 16 + g * 16 + (lane & 15)] = c[CTL_PART / 16] = make_uint4(0, 0, 0, 0);
                }
                if (lane < 3) ((uint4*)state)[lane] = make_uint4(0, 0, 0, 0);
            }
        } else {
            const int u = rk & 7;
            const bool isV = rk >= 8;
            const int tfirst = isV ? 1 : 2;
            const int* base = isV ? P.qv : P.qk;
            auto unit_ptr = [&](int t) { return base + ((size_t)((t >> 4) * NGROUP + grp) * SEQ + (t & 15) * 128 + u * 16) * DH; };
            if (warp == 1) {
#pragma unroll 1
                for (int i = 0; i < PFD; i++) {
                    wait_until(clk0, (isV ? PF_TV : PF_TK) + i * PF_DT);
                    l2_prefetch(unit_ptr(tfirst + i), 12288);
                }
#pragma unroll 1
                for (int t = tfirst; t < NT; t++) {
                    mbar_wait_sleep(sb + B_UNIT + 8 * (t & 7), ((t - tfirst) >> 3) & 1);
                    if (t + PFD < NT) l2_prefetch(unit_ptr(t + PFD), 12288);
                    if (lane == 0) {
                        TP(3, t);
                        publish(flags + 2 * t + (isV ? 3 : 0), u, 1 | lds_u32(sb + SM_QBIG) | (lds_u32(sb + SM_VBAD) >> (t >> 4) * 8 & 4));
                        TP(4, t);
                    }
                    __syncwarp();
                    if ((t & 15) == 11 && t < TOTAL - 16) put_v_offset(sb + SM_OFF + (t >> 4) * 16 + 16, v_offset(P, ((t >> 4) + 1) * NGROUP + grp, lane));
                }
            } else {
                const uint64_t pol = policy_evict_first();
                const int pw = warp < 4 ? warp - 2 : warp - 10, c = pw >> 1, h = pw & 1;
                const int hw = lane >> 4, l16 = lane & 15;
                const uint32_t soff = h * 3072 + c * 256 + hw * 768 + l16 * 16;
                const uint32_t doff = (u & 3) * 2048 + c * SUB + h * 512 + hw * 128 +
                                      (isV ? ((((l16 >> 3) * 4 + (l16 & 1)) ^ hw ^ (4 * h)) << 4) + ((l16 >> 1) & 3) * 4
                                           : (((l16 >> 1) ^ hw ^ (4 * h)) << 4) + (l16 & 1) * 8);
                put_v_offset(sb + SM_OFF, v_offset(P, grp, lane));
                wait_until(clk0, isV ? DQ_TV : DQ_TK);
#pragma unroll 1
                for (int t = tfirst; t < NT; t++) {
                    uint32_t n = 0;
                    while (true) {
                        int prog;
                        asm volatile("ld.acquire.cta.shared.u32 %0, [%1];" : "=r"(prog) : "r"(sb + SM_PROG) : "memory");
                        if (prog + LEAD >= t + (isV ? 1 : 0)) break;
                        if (++n > SPIN_LIMIT) __trap();
                        __nanosleep(WPOLL);
                    }
                    if (lane == 0 && pw == 0) { TP(2, t); }
                    const int head = (t >> 4) * NGROUP + grp;
                    const uint8_t* src = (const uint8_t*)unit_ptr(t) + soff;
                    uint8_t* slot = ring + ring_off(grp, t, rk >> 2);
                    if (isV) {
                        const size_t key0 = (size_t)head * SEQ + (t & 15) * 128 + u * 16;
                        const uint32_t voff = sb + SM_OFF + (t >> 4) * 16 + 8;
                        if (c != 0) part_v<false>(P, src, key0, h, slot, doff, pol, voff);
                        else if (!part_v<true>(P, src, key0, h, slot, doff, pol, voff)) { set_flag(sb + SM_QBIG); set_vbad(sb + SM_VBAD + (t >> 4)); }
                    } else {
                        const size_t so = ((size_t)head * 32 + (t & 15) * 2 + (u >> 2)) * DH + c * 64;
                        part_k(P, src, (const uint8_t*)(P.ks + so) + (uint32_t)((lane & 15) * 8), (const uint8_t*)(P.kz + so) + (uint32_t)((lane & 15) * 8),
                               slot, doff, pol, sb + SM_OFF + (t >> 4) * 16);
                    }
                    __syncwarp();
                    if (lane == 0) mbar_arrive(sb + B_UNIT + 8 * (t & 7));
                    const int b = ((t & 15) - (isV ? 9 : 10)) * 6 + pw;
                    if (b >= 0 && b < 16) {
                        mbar_wait(sb + B_QFULL + (b & 8), (t >> 4) & 1);
                        if (q8_big(sb + SM_Q + b * 3072)) {
                            set_flag(sb + SM_QBIG);
                            if (lds_u32(sb + SM_OFF + (t >> 4) * 16)) set_flag(sb + SM_REDO + (t >> 4));
                        }
                        __syncwarp();
                    }
                }
                    if (HELP && pw == 0) {
                        asm volatile("{\n.reg .pred p, q;\n.reg .u32 v, n, k;\nmov.u32 n, 0;\n"
                                     "LOOP:\nld.acquire.gpu.global.u32 v, [%0];\nand.b32 k, v, 1;\nsetp.ne.u32 p, k, 0;\n@p bra.uni DONE;\n"
                                     "add.u32 n, n, 1;\nsetp.gt.u32 q, n, %4;\n@q trap;\nnanosleep.u32 100;\nbra.uni LOOP;\n"
                                     "DONE:\nld.shared.u32 k, [%1];\nsetp.eq.u32 q, k, 0;\nand.b32 v, v, 4;\nsetp.ne.or.u32 q, v, 0, q;\n"
                                     "@q st.shared.u8 [%2], 2;\nbar.warp.sync 0xffffffff;\nelect.sync _|p, 0xffffffff;\n"
                                     "@p mbarrier.arrive.shared::cta.b64 _, [%3];\n}\n"
                                     ::"l"((const uint8_t*)flags + CTL_PART), "r"(sb + SM_OFF + 48), "r"(sb + SM_REDO + 3), "r"(sb + B_PFLAG), "n"(SPIN_LIMIT) : "memory");
                    }
            }
        }
        __syncwarp();
        cluster_arrive();
        cluster_wait();
    } else {
        const int cw = wg - 1, t128 = tid & 127, lane = tid & 31;
        cluster_arrive();
        {
            const int grp = blockIdx.x >> 4, rk = blockIdx.x & 15;
            uint8_t* ring = P.pages + (grp >> 1) * PAGE - (rk & 4) * 2048;
            const uint64_t pol = policy_evict_first();
            const int key0 = cw * 128 + (rk & 7) * 16;
            if (t128 == 0) { TS(cw, 71); }
            bool good = true;
            if (rk >= 8) good = start_v<1>(P, grp, (rk & 7) * 16, ring + ring_off(grp, 0, rk >> 2), (tid >> 5) - 4, lane, pol);
            else start_k(P, grp, key0, ring + ring_off(grp, cw, rk >> 2), t128 >> 5, lane, pol, KOFF);
            if (t128 == 0) { TS(cw, 73); }
            cluster_wait();
            if (!good) set_vbad(sb + SM_VBAD);
            bar_sync(3);
            if (t128 == 0) { TS(cw, 74); }
            if (tid == 128) {
                proxy_fence_global();
                asm volatile("fence.release.gpu;" ::: "memory");
                mbar_wait(sb + B_ROLE, 0);
                asm volatile("st.relaxed.gpu.global.u32 [%0], %1;"
                             ::"l"(P.pages + ctl_off(grp) + CTL_PROBE + (blockIdx.x >> 1) * 32 + (rk & 1) * 4), "r"((uint32_t)TILE_READY | (lds_u32(sb + SM_VBAD) & 4)) : "memory");
                q_first(&qmap, sb + SM_Q, lds_u32(sb + SM_ROLE) * 128, sb + B_QFULL);
                asm volatile("red.release.cta.shared.max.s32 [%0], %1;" ::"r"(sb + SM_PROG), "r"(0) : "memory");
            }
            if (t128 == 0) { TS(cw, 75); }
            __syncwarp();
        }
        asm volatile("setmaxnreg.inc.sync.aligned.u32 224;");
        const int bid = role();
        float o[96], s[64];
        uint32_t p[32];
        Softmax sm;
        sm.fast = true; sm.m0 = 0.f; sm.m1 = 0.f; sm.a0 = 0.f; sm.a1 = 0.f;
        uint32_t kslot = 0, kphase = 0;
        const uint32_t sl = sb & 0x3FFFF;
        const uint32_t qdesc = ((sl + SM_Q + cw * 24576) >> 4) | (1u << 16);
        const uint32_t kdesc0 = ((sl + SM_K) >> 4) | (1u << 16), vdesc0 = ((sl + SM_V) >> 4) | ((SUB >> 4) << 16);
        uint32_t rbar;
        asm volatile("{\n.reg .pred p;\nmapa.shared::cluster.u32 %0, %1, %2;\nsetp.ne.u32 p, %3, 0;\n@p mov.u32 %0, 0;\n}\n"
                     : "=r"(rbar) : "r"(sb + SM_BAR), "r"((t128 >> 5) % CLUSTER), "r"(t128 & ~(32 * (CLUSTER - 1))));
        auto release = [&](uint32_t off) {
            asm volatile("{\n.reg .pred p;\n.reg .u32 a;\nsetp.ne.u32 p, %0, 0;\nadd.u32 a, %0, %1;\n"
                         "@p mbarrier.arrive.shared::cluster.b64 _, [a];\n}\n" ::"r"(rbar), "r"(off) : "memory");
        };
        constexpr uint32_t OKE = B_KEMPTY - SM_BAR, OVE = B_VEMPTY - SM_BAR;
        const int w8 = __shfl_sync(0xffffffffu, (tid >> 5) - 4, 0);
        auto next_q = [&](int item) {
            asm volatile("{\n.reg .pred p;\nelect.sync _|p, 0xffffffff;\n"
                         "@p mbarrier.arrive.expect_tx.shared::cta.b64 _, [%2], 6144;\n"
                         "@p cp.async.bulk.tensor.4d.shared::cluster.global.mbarrier::complete_tx::bytes [%0], [%1, {%3, %3, %3, %4}], [%2];\n}\n"
                         ::"r"(sb + SM_Q + w8 * 6144), "l"(&qmap), "r"(sb + B_QFULL + 8 * cw), "r"(0), "r"((item * NCTA + bid) * 16 + w8 * 2) : "memory");
        };
        auto k_next = [&]() { if (++kslot == KSLOTS) { kslot = 0; kphase ^= 1; } };
        auto k_wait = [&]() { mbar_wait(sb + B_KFULL + 8 * kslot, kphase); };
        auto qk_chunk = [&](int c) {
            const uint32_t kd = kdesc0 + kslot * (SUB >> 4);
#pragma unroll
            for (int k = 0; k < 4; k++) wgmma_ss_n128(s, qdesc + c * 64 + k * 2, kd + k * 2, (c | k) != 0);
            wg_commit();
        };
        auto pv_half = [&](uint32_t vd, int h, int acc) {
#pragma unroll
            for (int k = 4 * h; k < 4 * h + 4; k++)
                wgmma_rs_n192_tb(o, p[4 * k], p[4 * k + 1], p[4 * k + 2], p[4 * k + 3], vd + k * 128, k == 0 ? acc : 1);
            wg_commit();
        };
        auto out_ptr = [&](int item) {
            const uint32_t tl = threadIdx.x & 127;
            __nv_bfloat16* d = P.out + (size_t)((item * NCTA + bid) * 128 + cw * 64) * DH +
                               (uint32_t)(((tl >> 5) * 16 + ((tl & 31) >> 2)) * DH + (tl & 3) * 8);
            asm volatile("" : "+l"(d));
            return d;
        };
        auto v_back = [&](int item) { return __uint_as_float(lds_u32(sb + SM_OFF + item * 16 + 12)); };
        auto put_word = [&](__nv_bfloat16* d, int k, uint4 w) { __stcs((uint4*)(d + (k & 1) * 8 * DH + (k >> 1) * 32), w); };
        auto store_o = [&](__nv_bfloat16* d, float i0, float i1, float c, int n) {
#pragma unroll
            for (int k = 0; k < n; k++) put_word(d, k, out_word(o, k, i0, i1, c, c));
        };

#pragma unroll
        for (int i = 0; i < 96; i++) asm volatile("" : "=f"(o[i]));
        if (cw == 0) bar_arrive(1);

        if (t128 == 0) { TS(cw, 77); }
        mbar_wait(sb + B_QFULL + 8 * cw, 0);
        if (t128 == 0) { TS(cw, 78); }
        k_wait();
        if (t128 == 0) { TS(cw, 79); }
        bar_sync(1 + cw);
        wg_fence();
        qk_chunk(0); k_next(); k_wait(); qk_chunk(1); k_next(); k_wait(); qk_chunk(2); k_next();
        bar_arrive(1 + (cw ^ 1));
        wg_wait<2>(); release(OKE); wg_wait<1>(); release(OKE + 8); wg_wait<0>(); release(OKE + 16);
        fence_regs(s);
        sm.run<true>(s);
        sm.pack(s, p);

        constexpr int NOW = 9;
        float i0, i1, vb;
        __nv_bfloat16* d;
        auto step = [&](int t, auto LAST, auto FIRST) {
            constexpr bool last = decltype(LAST)::value;
            constexpr bool first = decltype(FIRST)::value;
            const uint32_t vd = vdesc0 + (t & 1) * (TILE >> 4);
            uint4 w[12 - NOW];
            if (last) {
                d = out_ptr(t >> 4);
                sm.finish(i0, i1, sb + SM_REDO + (t >> 4));
                vb = v_back(t >> 4);
                mbar_wait(sb + B_QFULL + 8 * cw, ((t + 1) >> 4) & 1);
            }
            k_wait();
            bar_sync(1 + cw);
            TF(0);
            fence_regs(p);
            wg_fence();
            const uint32_t e0 = kslot; qk_chunk(0); k_next(); k_wait();
            const uint32_t e1 = kslot; qk_chunk(1); k_next(); k_wait();
            const uint32_t e2 = kslot; qk_chunk(2); k_next();
            TF(1);
            if (first) {
                fence_regs(o);
#pragma unroll
                for (int k = 0; k < 12 - NOW; k++) {
                    w[k] = out_word(o, NOW + k, i0, i1, vb, vb);
                    asm volatile("" : "+r"(w[k].x), "+r"(w[k].y), "+r"(w[k].z), "+r"(w[k].w));
                }
            } else sm.rescale(o);
            fence_regs(o);
            wg_wait<2>(); release(OKE + 8 * e0);
            TF(2);
            mbar_wait(sb + B_VFULL + 8 * (t & 1), (t >> 1) & 1);
            wg_fence();
            pv_half(vd, 0, !first && (last || t != 0));
            wg_wait<2>(); release(OKE + 8 * e1);
            pv_half(vd, 1, 1);
            bar_arrive(1 + (cw ^ 1));
            TF(3);
            wg_wait<2>(); release(OKE + 8 * e2);
            TF(4);
            if (!last && !first && (t & 15) == 14 && t < TOTAL - 2) next_q((t >> 4) + 1);
            fence_regs(s);
            sm.run<last>(s);
            fence_regs(s);
            TF(5);
            wg_wait<0>();
            release(OVE + 8 * (t & 1));
            if (first) {
#pragma unroll
                for (int k = 0; k < 12 - NOW; k++) put_word(d, NOW + k, w[k]);
            }
            fence_regs(o);
            if (last) store_o(d, i0, i1, vb, NOW);
            TF(6);
            sm.pack(s, p);
            fence_regs(p);
            TF(7);
        };
#pragma unroll 1
        for (int t = 0;;) {
#pragma unroll 1
            do { step(t, Flag<false>(), Flag<false>()); t++; } while ((t & 15) != 15 && (!HELP || t != NT - 1));
            if (t == NT - 1) break;
            step(t, Flag<true>(), Flag<false>());
            step(t + 1, Flag<false>(), Flag<true>());
            t += 2;
        }
        {
            constexpr int t = NT - 1;
            const uint32_t vd = vdesc0 + (((t & 1) * (TILE >> 4)) ^ P.zero);
            d = out_ptr(3);
            TS(cw, 72);
            sm.rescale(o);
            float f0, f1;
            sm.sums(f0, f1, sb + SM_REDO + 3);
            if (HELP && !sm.fast) set_flag(sb + SM_REDO + 3);
            vb = v_back(3);
            mbar_wait(sb + B_VFULL + 8 * (t & 1), (t >> 1) & 1);
            bar_sync(1 + cw);
            fence_regs(o); fence_regs(p);
            wg_fence();
            pv_half(vd, 0, 1); pv_half(vd, 1, 1);
            bar_arrive(2 + cw);
            constexpr float VS = 1.f / (float)(1 << -VEXP);
            float c0 = vb, c1 = vb;
            uint4 hp[12];
            if (HELP) {
                constexpr uint32_t J = NT * 3;
                const uint32_t a0 = sb + SM_K + (cw ? (J + 2) % KSLOTS : J % KSLOTS) * SUB + (threadIdx.x & 127) * 16;
                const uint32_t a1 = sb + SM_K + (cw ? (J + 3) % KSLOTS : (J + 1) % KSLOTS) * SUB + (threadIdx.x & 127) * 16;
                mbar_wait(sb + B_PART + 8 * cw, 0);
                const uint4 hv = lds_v4(a1 + 4 * 2048);
                const float2 hl = make_float2(__uint_as_float(hv.x), __uint_as_float(hv.y));
#pragma unroll
                for (int k = 0; k < 12; k++) hp[k] = lds_v4((k < 8 ? a0 : a1 - 8 * 2048) + k * 2048);
                i0 = rcp((f0 + hl.x) * VS); i1 = rcp((f1 + hl.y) * VS);
                const float w0 = hl.x * VS * i0, w1 = hl.y * VS * i1;
                c0 = fmaf(-vb, w0, vb); c1 = fmaf(-vb, w1, vb);
                const uint32_t u0 = pack_bf16(w0, w0), u1 = pack_bf16(w1, w1);
#pragma unroll
                for (int k = 0; k < 12; k++) {
                    const uint32_t u = (k & 1) ? u1 : u0;
                    hp[k] = make_uint4(bf2_mul(hp[k].x, u), bf2_mul(hp[k].y, u), bf2_mul(hp[k].z, u), bf2_mul(hp[k].w, u));
                    asm volatile("" : "+r"(hp[k].x), "+r"(hp[k].y), "+r"(hp[k].z), "+r"(hp[k].w));
                }
            } else { i0 = rcp(f0 * VS); i1 = rcp(f1 * VS); }
            wg_wait<0>();
            TS(cw, 76);
            cluster_arrive();
            fence_regs(o);
            uint32_t x[12];
#pragma unroll
            for (int k = 0; k < 12; k++) {
                const uint32_t z = k < 2 ? 0 : x[k - 2] & P.zero;
                uint4 w = out_word(o, k, i0, i1, __uint_as_float(__float_as_uint(c0) ^ z), __uint_as_float(__float_as_uint(c1) ^ z));
                if (HELP) w = make_uint4(bf2_add(w.x, hp[k].x), bf2_add(w.y, hp[k].y), bf2_add(w.z, hp[k].z), bf2_add(w.w, hp[k].w));
                put_word(d, k, w);
                x[k] = w.w;
            }
        }
        if (cw == 0) bar_sync(3);
        uint32_t redo = lds_u32(sb + SM_REDO), qphase = 0;
        if (redo) bar_sync(4);
#pragma unroll 1
        for (int item = 0; redo; item++, redo >>= 8) {
            if (!(redo & 255)) continue;
            uint8_t* img = smem_raw + (sb - smem_u32(smem_raw));
            const uint64_t pol = policy_evict_first();
            const int head = item * NGROUP + (bid >> 4);
            next_q(item);
            sm.fast = false; sm.m0 = -INFINITY; sm.m1 = -INFINITY; sm.l0 = 0.f; sm.l1 = 0.f;
#pragma unroll 1
            for (int t = 0; t < 16; t++) {
#pragma unroll 2
                for (int a = 0; a < 4; a++) start_k(P, head, t * 128 + (2 * a + cw) * 16, img + SM_K, w8 & 3, lane, pol, 0.f);
#pragma unroll 4
                for (int a = 0; a < 8; a++) start_v<0>(P, head, t * 128 + a * 16, img + SM_V, w8, lane, pol);
                asm volatile("fence.proxy.async.shared::cta;" ::: "memory");
                bar_sync(3);
                mbar_wait(sb + B_QFULL + 8 * cw, qphase);
                wg_fence();
                kslot = 0; qk_chunk(0); kslot = 1; qk_chunk(1); kslot = 2; qk_chunk(2);
                wg_wait<0>();
                fence_regs(s);
                sm.run<false>(s);
                sm.pack(s, p);
                sm.rescale(o);
                fence_regs(o); fence_regs(p);
                wg_fence();
                pv_half(vdesc0, 0, t != 0); pv_half(vdesc0, 1, 1);
                wg_wait<0>();
                fence_regs(o);
                bar_sync(3);
            }
            sm.finish(i0, i1, sb + SM_REDO + 4);
            store_o(out_ptr(item), i0, i1, 0.f, 12);
            qphase ^= 1;
        }
        cluster_wait();
    }
}

typedef CUresult (*EncodeFn)(CUtensorMap*, CUtensorMapDataType, cuuint32_t, void*, const cuuint64_t*, const cuuint64_t*,
                             const cuuint32_t*, const cuuint32_t*, CUtensorMapInterleave, CUtensorMapSwizzle,
                             CUtensorMapL2promotion, CUtensorMapFloatOOBfill);

}

extern "C" void kernel_launch(void* const* d_in, const int* in_sizes, int n_in, void* d_out, int out_size) {
    cudaLaunchConfig_t cfg = {};
    cudaLaunchAttribute at[1];
    at[0].id = cudaLaunchAttributeClusterDimension;
    at[0].val.clusterDim.x = CLUSTER; at[0].val.clusterDim.y = 1; at[0].val.clusterDim.z = 1;
    cfg.attrs = at; cfg.numAttrs = 1;
    cfg.blockDim = dim3(512); cfg.dynamicSmemBytes = SMEM_BYTES; cfg.stream = cudaStreamPerThread;

    static EncodeFn encode = nullptr;
    static uintptr_t scratch, part;
    static bool help;
    if (!encode) {
        void* fn = nullptr;
        cudaDriverEntryPointQueryResult st;
        cudaGetDriverEntryPoint("cuTensorMapEncodeTiled", &fn, cudaEnableDefault, &st);
        encode = (EncodeFn)fn;
        cudaFuncSetAttribute(kvq_attn_kernel<false>, cudaFuncAttributeMaxDynamicSharedMemorySize, SMEM_BYTES);
        cudaFuncSetAttribute(kvq_attn_kernel<true>, cudaFuncAttributeMaxDynamicSharedMemorySize, SMEM_BYTES);
        int clusters = 0;
        cfg.gridDim = dim3(NCTA + NHELP);
        help = cudaOccupancyMaxActiveClusters(&clusters, kvq_attn_kernel<true>, &cfg) == cudaSuccess && clusters * CLUSTER >= NCTA + NHELP;
        cudaGetSymbolAddress((void**)&scratch, g_scratch);
        cudaGetSymbolAddress((void**)&part, g_part);
    }
    CUtensorMap qmap;
    const cuuint64_t gdim[4] = {64, 8, 3, (cuuint64_t)NH * SEQ / 8};
    const cuuint64_t gstride[3] = {DH * 2, 128, 8 * DH * 2};
    const cuuint32_t box[4] = {64, 8, 3, 2};
    const cuuint32_t estr[4] = {1, 1, 1, 1};
    encode(&qmap, CU_TENSOR_MAP_DATA_TYPE_BFLOAT16, 4, d_in[0], gdim, gstride, box, estr, CU_TENSOR_MAP_INTERLEAVE_NONE,
           CU_TENSOR_MAP_SWIZZLE_128B, CU_TENSOR_MAP_L2_PROMOTION_L2_128B, CU_TENSOR_MAP_FLOAT_OOB_FILL_NONE);
    Params P;
    P.q = (const __nv_bfloat16*)d_in[0];
    P.qk = (const int*)d_in[1]; P.qv = (const int*)d_in[2];
    P.ks = (const __nv_bfloat16*)d_in[3]; P.kz = (const __nv_bfloat16*)d_in[4];
    P.vs = (const __nv_bfloat16*)d_in[5]; P.vz = (const __nv_bfloat16*)d_in[6];
    P.out = (__nv_bfloat16*)d_out;
    P.pages = (uint8_t*)((scratch + PAGE - 1) & ~(uintptr_t)(PAGE - 1));
    P.part = (uint8_t*)part;
    P.zero = 0;
    cfg.gridDim = dim3(NCTA + (help ? NHELP : 0));
    cudaLaunchKernelEx(&cfg, help ? kvq_attn_kernel<true> : kvq_attn_kernel<false>, P, qmap);
}
```
